```python
import torch

def _softmax(x, axis=-1):
    return torch.softmax(x, dim=axis)
def _gelu(x):
    return torch.nn.functional.gelu(x, approximate="tanh")
def _silu(x):
    return torch.nn.functional.silu(x)
def _sigmoid(x):
    return torch.sigmoid(x)
def _layernorm(x, axis=-1, eps=1e-5):
    m = x.mean(dim=axis, keepdim=True)
    v = x.var(dim=axis, keepdim=True, unbiased=False)
    return (x - m) / torch.sqrt(v + eps)
def _scatter_add(tgt, idx, src, axis=0):
    return tgt.clone().index_add_(axis, idx, src)
def _segment_sum(src, seg, n):
    out = torch.zeros((n,) + src.shape[1:], dtype=src.dtype)
    return out.index_add_(0, seg, src)
def _pad(x, pw):
    flat = tuple(v for pair in reversed(pw) for v in pair)
    return torch.nn.functional.pad(x, flat)

kernel_name = 'interleave_layers__grouped_kv_mqa__glu_gated_geglu__prompt'

def setup_inputs():

    _w = (lambda a: (lambda t: t.to(torch.bfloat16) if t.is_floating_point() else t)(torch.as_tensor(a)))
    def _A_setup():
        B, S, D, H = 1, 2048, 448, 16
        Dh = D // H
        return {
            "x": _w((lambda *s: torch.randn(*s, dtype=torch.bfloat16) * 0.05)(B, S, D)),
            "wq": _w((lambda *s: torch.randn(*s, dtype=torch.bfloat16) * 0.05)(D, H * Dh)),
            "wk": _w((lambda *s: torch.randn(*s, dtype=torch.bfloat16) * 0.05)(D, Dh)),
            "wv": _w((lambda *s: torch.randn(*s, dtype=torch.bfloat16) * 0.05)(D, Dh)),
            "wo": _w((lambda *s: torch.randn(*s, dtype=torch.bfloat16) * 0.05)(H * Dh, D)),
        }
    _A_in = _A_setup()

    def _B_setup():
        B, S, Dm, Df = 1, 2048, 448, 1792
        return {
            "x": _w((lambda *s: torch.randn(*s, dtype=torch.bfloat16) * 0.05)(B, S, Dm)),
            "w_gate": _w((lambda *s: torch.randn(*s, dtype=torch.bfloat16) * 0.8)(Dm, Df) * (Dm ** -0.5)),
            "w_up": _w((lambda *s: torch.randn(*s, dtype=torch.bfloat16) * 0.8)(Dm, Df) * (Dm ** -0.5)),
            "w_down": _w((lambda *s: torch.randn(*s, dtype=torch.bfloat16) * 0.8)(Df, Dm) * (Df ** -0.5)),
        }
    _B_in = _B_setup()

    return {
        "A_x": _A_in["x"],
        "A_wq": _A_in["wq"],
        "A_wk": _A_in["wk"],
        "A_wv": _A_in["wv"],
        "A_wo": _A_in["wo"],
        "B_x": _B_in["x"],
        "B_w_gate": _B_in["w_gate"],
        "B_w_up": _B_in["w_up"],
        "B_w_down": _B_in["w_down"],
    }

def reference(A_x, A_wq, A_wk, A_wv, A_wo, B_x, B_w_gate, B_w_up, B_w_down):
    def _A_ref(x, wq, wk, wv, wo):
        B, S, D = x.shape
        H = 16
        Dh = D // H
        q = (lambda x, *d: x.permute(*d))((x @ wq).reshape(B, S, H, Dh), 0, 2, 1, 3)
        k = x @ wk
        v = x @ wv
        scores = torch.einsum("bhqd,bkd->bhqk", q, k) * (Dh ** -0.5)
        p = _softmax(scores, axis=-1)
        o = torch.einsum("bhqk,bkd->bhqd", p, v)
        return (lambda x, *d: x.permute(*d))(o, 0, 2, 1, 3).reshape(B, S, H * Dh) @ wo

    def _B_ref(x, w_gate, w_up, w_down):
        g = torch.einsum("bsd,df->bsf", x, w_gate)
        u = torch.einsum("bsd,df->bsf", x, w_up)
        h = _gelu(g) * u
        return torch.einsum("bsf,fd->bsd", h, w_down)

    x = A_x
    x = x + _A_ref(_layernorm(x, axis=-1), A_wq, A_wk, A_wv, A_wo)
    x = x + _B_ref(_layernorm(x, axis=-1), B_w_gate, B_w_up, B_w_down)
    x = x + _A_ref(_layernorm(x, axis=-1), A_wq, A_wk, A_wv, A_wo)
    x = x + _B_ref(_layernorm(x, axis=-1), B_w_gate, B_w_up, B_w_down)
    return x
```

```cpp
#include <cuda_runtime.h>
#include <cuda_bf16.h>
#include <cuda_fp16.h>
#include <stdint.h>

typedef __nv_bfloat16 bf16;

constexpr int SEQ = 2048, DM = 448, DFF = 1792;
constexpr float QSCALE = 0.18898223650461362f * 1.4426950408889634f;
constexpr float PSHIFT = 15.f;
constexpr float L_MIN = 128.f;

constexpr size_t O_KVH = 0;
constexpr size_t O_KVB = O_KVH + 16 * 16384;
constexpr size_t O_CNT = O_KVB + 16 * 16384;
constexpr size_t O_KVSTAT = O_CNT + 4096;
constexpr size_t O_CSQ = O_KVSTAT + 1024;
constexpr size_t O_CS = O_CSQ + 3072;
constexpr size_t O_ST0 = O_CS + 14336 + 1024;
constexpr size_t O_ST1 = O_ST0 + 131072;
constexpr size_t O_ST2 = O_ST1 + 131072;
constexpr size_t O_WQT = O_ST2 + 131072;
constexpr size_t O_WKVT = O_WQT + 8 * 57344;
constexpr size_t O_WOT = O_WKVT + 2 * 28672;
constexpr size_t O_W2T = O_WOT + 8 * 50176;
constexpr size_t O_W1T = O_W2T + 8 * 16 * 12544;
constexpr size_t O_X0 = O_W1T + 8 * 2 * 14 * 14336;
constexpr size_t O_O = O_X0 + SEQ * DM * 2;
constexpr size_t O_X1 = O_O + SEQ * DM * 2;
constexpr size_t O_X2 = O_X1 + SEQ * DM * 2;
constexpr size_t O_QB = O_X2 + SEQ * DM * 2;
constexpr size_t O_H = O_QB + 128 * 4 * 64 * 32 * 2;
constexpr size_t SCRATCH_BYTES = O_H + (size_t)SEQ * DFF * 2;
static_assert(O_ST0 % 1024 == 0 && O_WQT % 1024 == 0 && O_W1T % 128 == 0 && O_X0 % 128 == 0 && O_H % 128 == 0, "alignment");
__device__ __align__(1024) uint8_t g_scratch[SCRATCH_BYTES];
#define g_kvh (G + O_KVH)
#define g_kvb (G + O_KVB)
#define g_kvcnt ((unsigned*)(G + O_CNT))
#define g_x1cnt ((unsigned(*)[16])(G + O_CNT + 64))
#define g_hcnt ((unsigned(*)[16][16])(G + O_CNT + 256))
#define g_kvstat ((float4*)(G + O_KVSTAT))
#define g_csq ((float*)(G + O_CSQ))
#define g_cs ((float*)(G + O_CS))
#define g_st0 ((float2*)(G + O_ST0))
#define g_st1 ((float2*)(G + O_ST1))
#define g_st2 ((float2*)(G + O_ST2))
#define g_wqt (G + O_WQT)
#define g_wkvt (G + O_WKVT)
#define g_wot (G + O_WOT)
#define g_w2t (G + O_W2T)
#define g_w1t (G + O_W1T)
#define g_x0 (G + O_X0)
#define g_O (G + O_O)
#define g_x1 (G + O_X1)
#define g_x2 (G + O_X2)
#define g_qb ((bf16*)(G + O_QB))
#define g_h (G + O_H)

#define STAMP(kern, role, idx) do {} while (0)
#define STAMP2(role, idx) do {} while (0)
#define STAMPC(kern, role, idx) do {} while (0)
__device__ __forceinline__ uint32_t s2u(const void* p) { return (uint32_t)__cvta_generic_to_shared(p); }
__device__ __forceinline__ void mbar_init(uint32_t b, int c) { asm volatile("mbarrier.init.shared::cta.b64 [%0], %1;" :: "r"(b), "r"(c) : "memory"); }
__device__ __forceinline__ void mbar_expect(uint32_t b, uint32_t bytes) { asm volatile("mbarrier.arrive.expect_tx.shared::cta.b64 _, [%0], %1;" :: "r"(b), "r"(bytes) : "memory"); }
__device__ __forceinline__ void mbar_arrive(uint32_t b) { asm volatile("mbarrier.arrive.shared::cta.b64 _, [%0];" :: "r"(b) : "memory"); }
__device__ __forceinline__ void mbar_arrive_if(uint32_t b, bool p) {
  asm volatile("{\n.reg .pred q;\nsetp.ne.b32 q, %1, 0;\n@q mbarrier.arrive.shared::cta.b64 _, [%0];\n}" :: "r"(b), "r"((int)p) : "memory");
}
__device__ __forceinline__ void mbar_wait(uint32_t b, uint32_t ph) {
  asm volatile("{\n.reg .pred p;\n.reg .u32 n;\n"
               "mbarrier.try_wait.parity.shared::cta.b64 p, [%0], %1;\n@p bra MBW_DONE;\n"
               "mov.u32 n, 0;\n"
               "MBW_LOOP:\nmbarrier.try_wait.parity.shared::cta.b64 p, [%0], %1;\n@p bra MBW_DONE;\n"
               "add.u32 n, n, 1;\nsetp.lt.u32 p, n, 0x40000;\n@p bra MBW_LOOP;\n"
               "MBW_DONE:\n}" :: "r"(b), "r"(ph) : "memory");
}
__device__ __forceinline__ void bulk_g2s(uint32_t dst, const void* src, uint32_t bytes, uint32_t bar) {
  asm volatile("cp.async.bulk.shared::cluster.global.mbarrier::complete_tx::bytes [%0], [%1], %2, [%3];" :: "r"(dst), "l"(src), "r"(bytes), "r"(bar) : "memory");
}
__device__ __forceinline__ void bulk_s2g(void* dst, uint32_t src, uint32_t bytes) {
  asm volatile("cp.async.bulk.global.shared::cta.bulk_group [%0], [%1], %2;" :: "l"(dst), "r"(src), "r"(bytes) : "memory");
}
__device__ __forceinline__ void bulk_commit() { asm volatile("cp.async.bulk.commit_group;" ::: "memory"); }
__device__ __forceinline__ void bulk_wait0() { asm volatile("cp.async.bulk.wait_group 0;" ::: "memory"); }
__device__ __forceinline__ void bulk_wait0_read() { asm volatile("cp.async.bulk.wait_group.read 0;" ::: "memory"); }
__device__ __forceinline__ void prefetch_l2(const void* p, uint32_t bytes) { asm volatile("cp.async.bulk.prefetch.L2.global [%0], %1;" :: "l"(p), "r"(bytes) : "memory"); }
__device__ __forceinline__ void fence_async_smem() { asm volatile("fence.proxy.async.shared::cta;" ::: "memory"); }
__device__ __forceinline__ void fence_async_global() { asm volatile("fence.proxy.async.global;" ::: "memory"); }
__device__ __forceinline__ void named_bar(int id, int n) { asm volatile("bar.sync %0, %1;" :: "r"(id), "r"(n) : "memory"); }
__device__ __forceinline__ bool elect_one() {
  uint32_t p;
  asm volatile("{\n.reg .pred P;\nelect.sync _|P, 0xFFFFFFFF;\nselp.b32 %0, 1, 0, P;\n}" : "=r"(p));
  return p != 0;
}
__device__ __forceinline__ void pdl_launch() { asm volatile("griddepcontrol.launch_dependents;" ::: "memory"); }
__device__ __forceinline__ void pdl_wait() { asm volatile("griddepcontrol.wait;" ::: "memory"); }
__device__ __forceinline__ void red_release(unsigned* p, unsigned v) { asm volatile("red.release.gpu.global.add.u32 [%0], %1;" :: "l"(p), "r"(v) : "memory"); }
__device__ __forceinline__ void red_relaxed(unsigned* p, unsigned v) { asm volatile("red.relaxed.gpu.global.add.u32 [%0], %1;" :: "l"(p), "r"(v) : "memory"); }
__device__ __forceinline__ unsigned ld_acquire(const unsigned* p) { unsigned v; asm volatile("ld.acquire.gpu.global.u32 %0, [%1];" : "=r"(v) : "l"(p) : "memory"); return v; }
__device__ __forceinline__ unsigned ld_relaxed(const unsigned* p) { unsigned v; asm volatile("ld.relaxed.gpu.global.u32 %0, [%1];" : "=r"(v) : "l"(p) : "memory"); return v; }
__device__ __forceinline__ void fence_acquire() { asm volatile("fence.acquire.gpu;" ::: "memory"); }
__device__ __forceinline__ void poll_ge(const unsigned* p, unsigned target) {
  #pragma unroll 1
  for (uint32_t i = 0; i < (1u << 21); i++) { if (ld_relaxed(p) >= target) break; }
  fence_acquire();
}
__device__ __forceinline__ void poll_ge_warp(const unsigned* p, unsigned target) {
  #pragma unroll 1
  for (uint32_t i = 0; i < (1u << 21); i++) { if (__all_sync(~0u, ld_relaxed(p) >= target)) break; }
}
constexpr uint32_t SB0 = 1024;
__device__ __forceinline__ uint64_t mkdesc(uint32_t addr, uint32_t lbo, uint32_t sbo, uint32_t swz) {
  return (uint64_t)((addr & 0x3FFFF) >> 4) | ((uint64_t)(lbo >> 4) << 16) | ((uint64_t)(sbo >> 4) << 32) | ((uint64_t)swz << 62);
}
#define WG_FENCE() asm volatile("wgmma.fence.sync.aligned;" ::: "memory")
#define WG_COMMIT() asm volatile("wgmma.commit_group.sync.aligned;" ::: "memory")
#define WG_WAIT(n) asm volatile("wgmma.wait_group.sync.aligned %0;" :: "n"(n) : "memory")
template<int N> __device__ __forceinline__ void fence_regs(float* d) {
  #pragma unroll
  for (int i = 0; i < N; i++) asm volatile("" : "+f"(d[i]) :: "memory");
}
template<int N> __device__ __forceinline__ void fence_regs(uint32_t* d) {
  #pragma unroll
  for (int i = 0; i < N; i++) asm volatile("" : "+r"(d[i]) :: "memory");
}
template<int R> __device__ __forceinline__ void reg_alloc() { asm volatile("setmaxnreg.inc.sync.aligned.u32 %0;" :: "n"(R)); }
template<int R> __device__ __forceinline__ void reg_dealloc() { asm volatile("setmaxnreg.dec.sync.aligned.u32 %0;" :: "n"(R)); }
__device__ __forceinline__ float ex2f(float x) { float y; asm("ex2.approx.ftz.f32 %0, %1;" : "=f"(y) : "f"(x)); return y; }
__device__ __forceinline__ float sqrt_fast(float x) { float y; asm("sqrt.approx.f32 %0, %1;" : "=f"(y) : "f"(x)); return y; }
__device__ __forceinline__ float rcp_fast(float x) { float y; asm("rcp.approx.ftz.f32 %0, %1;" : "=f"(y) : "f"(x)); return y; }
__device__ __forceinline__ float tanhf_fast(float x) { float y; asm("tanh.approx.f32 %0, %1;" : "=f"(y) : "f"(x)); return y; }
__device__ __forceinline__ uint32_t pack_bf16(float lo, float hi) { uint32_t r; asm("cvt.rn.bf16x2.f32 %0, %1, %2;" : "=r"(r) : "f"(hi), "f"(lo)); return r; }
__device__ __forceinline__ uint32_t pack_f16(float lo, float hi) { uint32_t r; asm("cvt.rn.f16x2.f32 %0, %1, %2;" : "=r"(r) : "f"(hi), "f"(lo)); return r; }
__device__ __forceinline__ float bf_lo(uint32_t v) { return __uint_as_float(v << 16); }
__device__ __forceinline__ float bf_hi(uint32_t v) { return __uint_as_float(v & 0xFFFF0000u); }
__device__ __forceinline__ uint32_t hadd2(uint32_t a, uint32_t b) { uint32_t r; asm("add.rn.f16x2 %0, %1, %2;" : "=r"(r) : "r"(a), "r"(b)); return r; }
__device__ __forceinline__ uint32_t hsub2(uint32_t a, uint32_t b) { uint32_t r; asm("sub.rn.f16x2 %0, %1, %2;" : "=r"(r) : "r"(a), "r"(b)); return r; }
__device__ __forceinline__ uint32_t hfma2(uint32_t a, uint32_t b, uint32_t c) { uint32_t r; asm("fma.rn.f16x2 %0, %1, %2, %3;" : "=r"(r) : "r"(a), "r"(b), "r"(c)); return r; }
#define A_DEG 3
__device__ __forceinline__ uint32_t ex2_h2_poly(uint32_t x) {
  const uint32_t M = 0x66006600u;
  uint32_t t = hadd2(x, M);
  uint32_t j = hsub2(t, M);
  uint32_t f = hsub2(x, j);
  uint32_t p = hfma2(f, 0x2B102B10u, 0x33C333C3u);
  p = hfma2(p, f, 0x398C398Cu);
  p = hfma2(p, f, 0x3C003C00u);
  uint32_t sh;
  asm("shf.l.wrap.b32 %0, %1, %1, 10;" : "=r"(sh) : "r"(t));
  sh &= 0xFC00FC00u;
  return __viaddmax_s16x2(p, sh, 0);
}
__device__ __forceinline__ uint32_t ex2_h2_mufu(uint32_t x) { uint32_t y; asm("ex2.approx.f16x2 %0, %1;" : "=r"(y) : "r"(x)); return y; }
__device__ __forceinline__ void stmatrix_x4(uint32_t addr, uint32_t r0, uint32_t r1, uint32_t r2, uint32_t r3) {
  asm volatile("stmatrix.sync.aligned.m8n8.x4.shared.b16 [%0], {%1,%2,%3,%4};" :: "r"(addr), "r"(r0), "r"(r1), "r"(r2), "r"(r3) : "memory");
}
__device__ __forceinline__ uint4 ldg_nc128(const void* p) { uint4 v; asm volatile("ld.global.nc.v4.u32 {%0,%1,%2,%3}, [%4];" : "=r"(v.x), "=r"(v.y), "=r"(v.z), "=r"(v.w) : "l"(p)); return v; }
__device__ __forceinline__ uint32_t tiled_off(int row, int col) {
  return (row >> 7) * 114688 + (col / 112) * 28672 + ((row & 127) >> 3) * 1792 + ((col % 112) >> 3) * 128 + (row & 7) * 16 + (col & 7) * 2;
}
__device__ __forceinline__ uint2 ldg_nc64(const void* p) { uint2 v; asm volatile("ld.global.nc.v2.u32 {%0,%1}, [%2];" : "=r"(v.x), "=r"(v.y) : "l"(p)); return v; }

template<int SD> __device__ __forceinline__ void mma_qk_h64(uint32_t* d, uint64_t da, uint64_t db) {
  asm volatile("wgmma.mma_async.sync.aligned.m64n64k16.f16.f16.f16 {%0,%1,%2,%3,%4,%5,%6,%7,%8,%9,%10,%11,%12,%13,%14,%15}, %16, %17, %18, 1, 1, 0, 0;\n"
    : "+r"(d[0]),"+r"(d[1]),"+r"(d[2]),"+r"(d[3]),"+r"(d[4]),"+r"(d[5]),"+r"(d[6]),"+r"(d[7]),"+r"(d[8]),"+r"(d[9]),"+r"(d[10]),"+r"(d[11]),"+r"(d[12]),"+r"(d[13]),"+r"(d[14]),"+r"(d[15]) : "l"(da), "l"(db), "n"(SD));
}

template<int SD> __device__ __forceinline__ void mma_pv_h32(float* d, const uint32_t* a, uint64_t db) {
  asm volatile("wgmma.mma_async.sync.aligned.m64n32k16.f32.f16.f16 {%0,%1,%2,%3,%4,%5,%6,%7,%8,%9,%10,%11,%12,%13,%14,%15}, {%16,%17,%18,%19}, %20, %21, 1, 1, 1;\n"
    : "+f"(d[0]),"+f"(d[1]),"+f"(d[2]),"+f"(d[3]),"+f"(d[4]),"+f"(d[5]),"+f"(d[6]),"+f"(d[7]),"+f"(d[8]),"+f"(d[9]),"+f"(d[10]),"+f"(d[11]),"+f"(d[12]),"+f"(d[13]),"+f"(d[14]),"+f"(d[15]) : "r"(a[0]), "r"(a[1]), "r"(a[2]), "r"(a[3]), "l"(db), "n"(SD));
}

template<int SD> __device__ __forceinline__ void mma_qk_b64(float* d, const uint32_t* a, uint64_t db) {
  asm volatile("wgmma.mma_async.sync.aligned.m64n64k16.f32.bf16.bf16 {%0,%1,%2,%3,%4,%5,%6,%7,%8,%9,%10,%11,%12,%13,%14,%15,%16,%17,%18,%19,%20,%21,%22,%23,%24,%25,%26,%27,%28,%29,%30,%31}, {%32,%33,%34,%35}, %36, %37, 1, 1, 0;\n"
    : "+f"(d[0]),"+f"(d[1]),"+f"(d[2]),"+f"(d[3]),"+f"(d[4]),"+f"(d[5]),"+f"(d[6]),"+f"(d[7]),"+f"(d[8]),"+f"(d[9]),"+f"(d[10]),"+f"(d[11]),"+f"(d[12]),"+f"(d[13]),"+f"(d[14]),"+f"(d[15]),"+f"(d[16]),"+f"(d[17]),"+f"(d[18]),"+f"(d[19]),"+f"(d[20]),"+f"(d[21]),"+f"(d[22]),"+f"(d[23]),"+f"(d[24]),"+f"(d[25]),"+f"(d[26]),"+f"(d[27]),"+f"(d[28]),"+f"(d[29]),"+f"(d[30]),"+f"(d[31]) : "r"(a[0]), "r"(a[1]), "r"(a[2]), "r"(a[3]), "l"(db), "n"(SD));
}

template<int SD> __device__ __forceinline__ void mma_pv_b32(float* d, const uint32_t* a, uint64_t db) {
  asm volatile("wgmma.mma_async.sync.aligned.m64n32k16.f32.bf16.bf16 {%0,%1,%2,%3,%4,%5,%6,%7,%8,%9,%10,%11,%12,%13,%14,%15}, {%16,%17,%18,%19}, %20, %21, 1, 1, 1;\n"
    : "+f"(d[0]),"+f"(d[1]),"+f"(d[2]),"+f"(d[3]),"+f"(d[4]),"+f"(d[5]),"+f"(d[6]),"+f"(d[7]),"+f"(d[8]),"+f"(d[9]),"+f"(d[10]),"+f"(d[11]),"+f"(d[12]),"+f"(d[13]),"+f"(d[14]),"+f"(d[15]) : "r"(a[0]), "r"(a[1]), "r"(a[2]), "r"(a[3]), "l"(db), "n"(SD));
}

__device__ __forceinline__ void mma_b64_tb(float* d, uint64_t da, uint64_t db, int sd) {
  asm volatile("{\n.reg .pred p;\nsetp.ne.b32 p, %34, 0;\n"
    "wgmma.mma_async.sync.aligned.m64n64k16.f32.bf16.bf16 {%0,%1,%2,%3,%4,%5,%6,%7,%8,%9,%10,%11,%12,%13,%14,%15,%16,%17,%18,%19,%20,%21,%22,%23,%24,%25,%26,%27,%28,%29,%30,%31}, %32, %33, p, 1, 1, 0, 1;\n}\n"
    : "+f"(d[0]),"+f"(d[1]),"+f"(d[2]),"+f"(d[3]),"+f"(d[4]),"+f"(d[5]),"+f"(d[6]),"+f"(d[7]),"+f"(d[8]),"+f"(d[9]),"+f"(d[10]),"+f"(d[11]),"+f"(d[12]),"+f"(d[13]),"+f"(d[14]),"+f"(d[15]),"+f"(d[16]),"+f"(d[17]),"+f"(d[18]),"+f"(d[19]),"+f"(d[20]),"+f"(d[21]),"+f"(d[22]),"+f"(d[23]),"+f"(d[24]),"+f"(d[25]),"+f"(d[26]),"+f"(d[27]),"+f"(d[28]),"+f"(d[29]),"+f"(d[30]),"+f"(d[31]) : "l"(da), "l"(db), "r"(sd));
}

__device__ __forceinline__ void mma_b32_tb(float* d, uint64_t da, uint64_t db, int sd) {
  asm volatile("{\n.reg .pred p;\nsetp.ne.b32 p, %18, 0;\n"
    "wgmma.mma_async.sync.aligned.m64n32k16.f32.bf16.bf16 {%0,%1,%2,%3,%4,%5,%6,%7,%8,%9,%10,%11,%12,%13,%14,%15}, %16, %17, p, 1, 1, 0, 1;\n}\n"
    : "+f"(d[0]),"+f"(d[1]),"+f"(d[2]),"+f"(d[3]),"+f"(d[4]),"+f"(d[5]),"+f"(d[6]),"+f"(d[7]),"+f"(d[8]),"+f"(d[9]),"+f"(d[10]),"+f"(d[11]),"+f"(d[12]),"+f"(d[13]),"+f"(d[14]),"+f"(d[15]) : "l"(da), "l"(db), "r"(sd));
}

__device__ __forceinline__ void mma_b224_tb(float* d, uint64_t da, uint64_t db, int sd) {
  asm volatile("{\n.reg .pred p;\nsetp.ne.b32 p, %114, 0;\n"
    "wgmma.mma_async.sync.aligned.m64n224k16.f32.bf16.bf16 {%0,%1,%2,%3,%4,%5,%6,%7,%8,%9,%10,%11,%12,%13,%14,%15,%16,%17,%18,%19,%20,%21,%22,%23,%24,%25,%26,%27,%28,%29,%30,%31,%32,%33,%34,%35,%36,%37,%38,%39,%40,%41,%42,%43,%44,%45,%46,%47,%48,%49,%50,%51,%52,%53,%54,%55,%56,%57,%58,%59,%60,%61,%62,%63,%64,%65,%66,%67,%68,%69,%70,%71,%72,%73,%74,%75,%76,%77,%78,%79,%80,%81,%82,%83,%84,%85,%86,%87,%88,%89,%90,%91,%92,%93,%94,%95,%96,%97,%98,%99,%100,%101,%102,%103,%104,%105,%106,%107,%108,%109,%110,%111}, %112, %113, p, 1, 1, 0, 1;\n}\n"
    : "+f"(d[0]),"+f"(d[1]),"+f"(d[2]),"+f"(d[3]),"+f"(d[4]),"+f"(d[5]),"+f"(d[6]),"+f"(d[7]),"+f"(d[8]),"+f"(d[9]),"+f"(d[10]),"+f"(d[11]),"+f"(d[12]),"+f"(d[13]),"+f"(d[14]),"+f"(d[15]),"+f"(d[16]),"+f"(d[17]),"+f"(d[18]),"+f"(d[19]),"+f"(d[20]),"+f"(d[21]),"+f"(d[22]),"+f"(d[23]),"+f"(d[24]),"+f"(d[25]),"+f"(d[26]),"+f"(d[27]),"+f"(d[28]),"+f"(d[29]),"+f"(d[30]),"+f"(d[31]),"+f"(d[32]),"+f"(d[33]),"+f"(d[34]),"+f"(d[35]),"+f"(d[36]),"+f"(d[37]),"+f"(d[38]),"+f"(d[39]),"+f"(d[40]),"+f"(d[41]),"+f"(d[42]),"+f"(d[43]),"+f"(d[44]),"+f"(d[45]),"+f"(d[46]),"+f"(d[47]),"+f"(d[48]),"+f"(d[49]),"+f"(d[50]),"+f"(d[51]),"+f"(d[52]),"+f"(d[53]),"+f"(d[54]),"+f"(d[55]),"+f"(d[56]),"+f"(d[57]),"+f"(d[58]),"+f"(d[59]),"+f"(d[60]),"+f"(d[61]),"+f"(d[62]),"+f"(d[63]),"+f"(d[64]),"+f"(d[65]),"+f"(d[66]),"+f"(d[67]),"+f"(d[68]),"+f"(d[69]),"+f"(d[70]),"+f"(d[71]),"+f"(d[72]),"+f"(d[73]),"+f"(d[74]),"+f"(d[75]),"+f"(d[76]),"+f"(d[77]),"+f"(d[78]),"+f"(d[79]),"+f"(d[80]),"+f"(d[81]),"+f"(d[82]),"+f"(d[83]),"+f"(d[84]),"+f"(d[85]),"+f"(d[86]),"+f"(d[87]),"+f"(d[88]),"+f"(d[89]),"+f"(d[90]),"+f"(d[91]),"+f"(d[92]),"+f"(d[93]),"+f"(d[94]),"+f"(d[95]),"+f"(d[96]),"+f"(d[97]),"+f"(d[98]),"+f"(d[99]),"+f"(d[100]),"+f"(d[101]),"+f"(d[102]),"+f"(d[103]),"+f"(d[104]),"+f"(d[105]),"+f"(d[106]),"+f"(d[107]),"+f"(d[108]),"+f"(d[109]),"+f"(d[110]),"+f"(d[111]) : "l"(da), "l"(db), "r"(sd));
}

__device__ __forceinline__ void mma_b56_tb(float* d, uint64_t da, uint64_t db, int sd) {
  asm volatile("{\n.reg .pred p;\nsetp.ne.b32 p, %30, 0;\n"
    "wgmma.mma_async.sync.aligned.m64n56k16.f32.bf16.bf16 {%0,%1,%2,%3,%4,%5,%6,%7,%8,%9,%10,%11,%12,%13,%14,%15,%16,%17,%18,%19,%20,%21,%22,%23,%24,%25,%26,%27}, %28, %29, p, 1, 1, 0, 1;\n}\n"
    : "+f"(d[0]),"+f"(d[1]),"+f"(d[2]),"+f"(d[3]),"+f"(d[4]),"+f"(d[5]),"+f"(d[6]),"+f"(d[7]),"+f"(d[8]),"+f"(d[9]),"+f"(d[10]),"+f"(d[11]),"+f"(d[12]),"+f"(d[13]),"+f"(d[14]),"+f"(d[15]),"+f"(d[16]),"+f"(d[17]),"+f"(d[18]),"+f"(d[19]),"+f"(d[20]),"+f"(d[21]),"+f"(d[22]),"+f"(d[23]),"+f"(d[24]),"+f"(d[25]),"+f"(d[26]),"+f"(d[27]) : "l"(da), "l"(db), "r"(sd));
}

namespace attn {
constexpr int TILE = 16384, NST = 12;
constexpr int X_OFF = 0, WQ_OFF = 114688, WKV_OFF = 172032;
constexpr int SCR_OFF = NST * TILE;
constexpr int Q_OFF = SCR_OFF + 16384;
constexpr int SM_OFF = Q_OFF + 16384;
constexpr int BAR_OFF = SM_OFF;
constexpr int MEAN_OFF = SM_OFF + 224;
constexpr int RSTD_OFF = MEAN_OFF + 512;
constexpr int CSQ_OFF = RSTD_OFF + 512;
constexpr int CSKV_OFF = CSQ_OFF + 256;
constexpr int QN_OFF = CSKV_OFF + 128;
constexpr int MISC_OFF = QN_OFF + 1024;
constexpr int SMEM = MISC_OFF + 64;
constexpr int KVS_OFF = 200704;
constexpr int SM2_OFF = 209152;
constexpr int B_X = 0  , B_KV0 = 112, B_KV1 = 120, B_KV2 = 128, B_KV3 = 136, B_EMPTY = 144, B_WQ = 152, B_SLOW = 160,
              B_WKV = 168, B_ST = 176  , B_CSQ = 192, B_MMA = 200;
#define A_PAT 0x5555
#define A_STRUCT 1
constexpr uint32_t PAT = A_PAT;

template<int I0, int N> __device__ __forceinline__ void exp_part(const uint32_t* s, uint32_t* p) {
  #pragma unroll
  for (int i = I0; i < I0 + N; i++) p[i] = ((PAT >> i) & 1) ? ex2_h2_poly(s[i]) : ex2_h2_mufu(s[i]);
}
__device__ __forceinline__ void exp_block(const uint32_t* s, uint32_t* p) { exp_part<0, 16>(s, p); }

__device__ __forceinline__ void write_O(uint8_t* __restrict__ G, const float* O, int t, int r, int wg) {
  const int lane = threadIdx.x % 32, warp = (threadIdx.x % 128) / 32, g = lane / 4, c = lane % 4;
  const float l0 = __shfl_sync(~0u, O[12], (lane & ~3) | 2), l1 = __shfl_sync(~0u, O[14], (lane & ~3) | 2);
  const float i0 = rcp_fast(l0), i1 = rcp_fast(l1);
  const int tok = t * 128 + (wg & 1) * 64 + warp * 16 + g, col = 56 * r + 28 * (wg >> 1) + 2 * c;
  #pragma unroll
  for (int j = 0; j < 4; j++) {
    if (j < 3 || c < 2) {
      const uint32_t o = tiled_off(tok, col + 8 * j);
      *(uint32_t*)(g_O + o) = pack_bf16(O[4 * j] * i0, O[4 * j + 1] * i0);
      *(uint32_t*)(g_O + o + 1792) = pack_bf16(O[4 * j + 2] * i1, O[4 * j + 3] * i1);
    }
  }
}

__device__ __forceinline__ void mma16816(float* d, const uint32_t* a, uint32_t b0, uint32_t b1) {
  asm volatile("mma.sync.aligned.m16n8k16.row.col.f32.bf16.bf16.f32 {%0,%1,%2,%3}, {%4,%5,%6,%7}, {%8,%9}, {%0,%1,%2,%3};"
               : "+f"(d[0]), "+f"(d[1]), "+f"(d[2]), "+f"(d[3]) : "r"(a[0]), "r"(a[1]), "r"(a[2]), "r"(a[3]), "r"(b0), "r"(b1));
}
__device__ __forceinline__ void slow_path(uint8_t* __restrict__ G, const uint8_t* smem, uint32_t sb, int wg, int cta) {
  const int lane = threadIdx.x % 32, warp = (threadIdx.x % 128) / 32, g = lane / 4, c = lane % 4;
  const uint32_t bar = sb + BAR_OFF + B_SLOW;
  if (threadIdx.x == 0) fence_async_global();
  uint32_t q[2][4];
  const bf16* qb = g_qb + ((size_t)(cta * 4 + wg) * 64 + warp * 16) * 32;
  #pragma unroll
  for (int ks = 0; ks < 2; ks++) {
    q[ks][0] = *(const uint32_t*)(qb + g * 32 + ks * 16 + 2 * c);
    q[ks][1] = *(const uint32_t*)(qb + (g + 8) * 32 + ks * 16 + 2 * c);
    q[ks][2] = *(const uint32_t*)(qb + g * 32 + ks * 16 + 2 * c + 8);
    q[ks][3] = *(const uint32_t*)(qb + (g + 8) * 32 + ks * 16 + 2 * c + 8);
  }
  float O[16];
  #pragma unroll
  for (int i = 0; i < 16; i++) O[i] = 0.f;
  float m0 = -INFINITY, m1 = -INFINITY;
  #pragma unroll 1
  for (int j = 0; j < 16; j++) {
    __syncthreads();
    if (threadIdx.x == 0) { mbar_expect(bar, TILE); bulk_g2s(sb, g_kvb + (size_t)j * TILE, TILE, bar); }
    mbar_wait(bar, j & 1);
    #pragma unroll 1
    for (int kb = 0; kb < 8; kb++) {
      float S[8] = {0.f, 0.f, 0.f, 0.f, 0.f, 0.f, 0.f, 0.f};
      #pragma unroll
      for (int nb = 0; nb < 2; nb++) {
        const uint8_t* kp = smem + (2 * kb + nb) * 512 + g * 16 + c * 4;
        mma16816(S + 4 * nb, q[0], *(const uint32_t*)kp, *(const uint32_t*)(kp + 128));
        mma16816(S + 4 * nb, q[1], *(const uint32_t*)(kp + 256), *(const uint32_t*)(kp + 384));
      }
      float x0 = fmaxf(fmaxf(S[0], S[1]), fmaxf(S[4], S[5])), x1 = fmaxf(fmaxf(S[2], S[3]), fmaxf(S[6], S[7]));
      x0 = fmaxf(x0, __shfl_xor_sync(~0u, x0, 1)); x0 = fmaxf(x0, __shfl_xor_sync(~0u, x0, 2));
      x1 = fmaxf(x1, __shfl_xor_sync(~0u, x1, 1)); x1 = fmaxf(x1, __shfl_xor_sync(~0u, x1, 2));
      const float n0 = fmaxf(m0, x0), n1 = fmaxf(m1, x1);
      const float a0 = (m0 == n0) ? 1.f : exp2f(m0 - n0), a1 = (m1 == n1) ? 1.f : exp2f(m1 - n1);
      m0 = n0; m1 = n1;
      uint32_t P[4];
      P[0] = pack_bf16(exp2f(S[0] - m0), exp2f(S[1] - m0)); P[1] = pack_bf16(exp2f(S[2] - m1), exp2f(S[3] - m1));
      P[2] = pack_bf16(exp2f(S[4] - m0), exp2f(S[5] - m0)); P[3] = pack_bf16(exp2f(S[6] - m1), exp2f(S[7] - m1));
      #pragma unroll
      for (int nb = 0; nb < 4; nb++) {
        O[4 * nb] *= a0; O[4 * nb + 1] *= a0; O[4 * nb + 2] *= a1; O[4 * nb + 3] *= a1;
        uint32_t b0, b1;
        asm volatile("ldmatrix.sync.aligned.m8n8.x2.trans.shared.b16 {%0,%1}, [%2];" : "=r"(b0), "=r"(b1)
                     : "r"(sb + 8192 + (2 * kb + ((lane >> 3) & 1)) * 512 + nb * 128 + (lane & 7) * 16));
        mma16816(O + 4 * nb, P, b0, b1);
      }
    }
  }
  write_O(G, O, cta / 8, cta % 8, wg);
}
}

__global__ void __launch_bounds__(512, 1) prep_kernel(uint8_t* __restrict__ G, const bf16* __restrict__ x0, const bf16* __restrict__ wq, const bf16* __restrict__ wk,
                                                      const bf16* __restrict__ wv) {
  __shared__ float s_part[16][8];
  const int tid = threadIdx.x, lane = tid % 32, wid = tid / 32, b = blockIdx.x;
  if (tid == 0) pdl_launch();
  uint4 w = make_uint4(0u, 0u, 0u, 0u);
  if (tid < DM) {
    if (b < 64) {
      const int col = 56 * (b >> 3) + 8 * (b & 7);
      if (col < DM) w = ldg_nc128(wq + (size_t)tid * DM + col);
    } else if (b < 72) {
      const bf16* src = ((b & 4) ? wv : wk) + (size_t)tid * 28 + 8 * (b & 3);
      const uint2 lo = ldg_nc64(src);
      uint2 hi = make_uint2(0u, 0u);
      if ((b & 3) < 3) hi = ldg_nc64(src + 4);
      w = make_uint4(lo.x, lo.y, hi.x, hi.y);
    }
  }
  const int row = b * 16 + wid;
  const uint8_t* xs = (const uint8_t*)x0 + (size_t)row * (DM * 2);
  const uint4 v0 = ldg_nc128(xs + lane * 16);
  uint4 v1 = make_uint4(0u, 0u, 0u, 0u);
  if (lane < 24) v1 = ldg_nc128(xs + (lane + 32) * 16);
  *(uint4*)(g_x0 + tiled_off(row, lane * 8)) = v0;
  if (lane < 24) *(uint4*)(g_x0 + tiled_off(row, (lane + 32) * 8)) = v1;
  {
    const uint32_t q[8] = {v0.x, v0.y, v0.z, v0.w, v1.x, v1.y, v1.z, v1.w};
    float sum = 0.f, sq = 0.f;
    #pragma unroll
    for (int e = 0; e < 8; e++) { const float a = bf_lo(q[e]), c = bf_hi(q[e]); sum += a + c; sq = fmaf(a, a, fmaf(c, c, sq)); }
    #pragma unroll
    for (int o = 1; o < 32; o <<= 1) { sum += __shfl_xor_sync(~0u, sum, o); sq += __shfl_xor_sync(~0u, sq, o); }
    if (lane < 8) g_st0[((row >> 7) * 8 + lane) * 128 + (row & 127)] = lane == 0 ? make_float2(sum, sq) : make_float2(0.f, 0.f);
  }
  if (b < 72) {
    if (tid < DM) {
      if (b < 64) *(uint4*)(g_wqt + (b >> 3) * 57344 + tid * 128 + (((b & 7) ^ (tid & 7)) * 16)) = w;
      else *(uint4*)(g_wkvt + ((b >> 2) & 1) * 28672 + (tid / 8) * 512 + (b & 3) * 128 + (tid % 8) * 16) = w;
    }
    float c8[8] = {bf_lo(w.x), bf_hi(w.x), bf_lo(w.y), bf_hi(w.y), bf_lo(w.z), bf_hi(w.z), bf_lo(w.w), bf_hi(w.w)};
    #pragma unroll
    for (int e = 0; e < 8; e++) {
      #pragma unroll
      for (int o = 1; o < 32; o <<= 1) c8[e] += __shfl_xor_sync(~0u, c8[e], o);
    }
    if (lane == 0) {
      #pragma unroll
      for (int e = 0; e < 8; e++) s_part[wid][e] = c8[e];
    }
    __syncthreads();
    if (tid < 8) {
      float sum = 0.f;
      #pragma unroll
      for (int i = 0; i < 16; i++) sum += s_part[i][tid];
      g_csq[(b < 64 ? b * 8 : 512 + (b - 64) * 8) + tid] = sum;
    }
  }
}

__global__ void __launch_bounds__(512, 1) attn_kernel(uint8_t* __restrict__ G, const bf16* __restrict__ wo,
                                                      const bf16* __restrict__ wgate, const bf16* __restrict__ wup, const bf16* __restrict__ wdown,
                                                      int layer) {
  using namespace attn;
  extern __shared__ __align__(1024) uint8_t smem[];
  const uint32_t sb = s2u(smem);
  const int tid = threadIdx.x, lane = tid % 32, wid = __shfl_sync(~0u, tid / 32, 0);
  const int wg = wid / 4, warp = wid % 4, g = lane / 4, c = lane % 4;
  const int t = blockIdx.x / 8, r = blockIdx.x % 8;
  const bool first = layer == 0;
  const uint32_t bb = sb + BAR_OFF;
  float* s_mean = (float*)(smem + MEAN_OFF);
  float* s_rstd = (float*)(smem + RSTD_OFF);
  float* s_csq = (float*)(smem + CSQ_OFF);
  float* s_cskv = (float*)(smem + CSKV_OFF);
  float* s_qn = (float*)(smem + QN_OFF);
  float* s_misc = (float*)(smem + MISC_OFF);
  if (tid % 128 == 0) { STAMPC(layer * 2, wg, 0); STAMP(layer * 2, wg, 15); }

  const bool duty = r < 4;
  const int dh = duty ? (r >> 1) : 0;
  auto load_x = [&](int h) {
    const uint8_t* xs = (first ? g_x0 : g_x2) + (size_t)t * 114688 + h * 14336;
    #pragma unroll
    for (int j = 0; j < 4; j++) { mbar_expect(bb + B_X + 8 * (2 * j + h), 14336); bulk_g2s(sb + X_OFF + j * 28672 + h * 14336, xs + j * 28672, 14336, bb + B_X + 8 * (2 * j + h)); }
  };
  if (wid == 15 && elect_one()) {
    #pragma unroll
    for (int i = 0; i < 26; i++) mbar_init(bb + 8 * i, i == 18 ? 16 : ((i == 22 || i == 23) ? 64 : (i == 25 ? 7 : 1)));
    asm volatile("fence.mbarrier_init.release.cluster;" ::: "memory");
    ((int*)s_misc)[4] = 0;
  }
  __syncthreads();
  if (wid == 15 && elect_one()) {
    pdl_launch();
    if (first) pdl_wait();
    if (duty) { mbar_expect(bb + B_WKV, 28672); bulk_g2s(sb + WKV_OFF, g_wkvt + (r & 1) * 28672, 28672, bb + B_WKV); }
    if (!first) pdl_wait();
    load_x(dh);
    mbar_expect(bb + B_WQ, 57344); bulk_g2s(sb + WQ_OFF, g_wqt + r * 57344, 57344, bb + B_WQ);
    if (!duty) load_x(1);
  }
  if (tid % 128 == 0) STAMPC(layer * 2, wg, 9);
  pdl_wait();
  if (wg == 2) {
    if (warp < 2) s_csq[tid - 256] = g_csq[r * 64 + tid - 256];
    else if (warp == 2 && duty) s_cskv[lane] = g_csq[512 + (r & 1) * 32 + lane];
  }
  if (tid % 128 == 0) STAMPC(layer * 2, wg, 1);
  if (blockIdx.x == 127 && tid >= 128 && tid < 128 + 272) {
    const int i = tid - 128;
    if (i < 256) (&g_hcnt[layer][0][0])[i] = 0; else g_x1cnt[layer][i - 256] = 0;
  }

  if (wg < 2) {
    float acc[32];
    #pragma unroll
    for (int i = 0; i < 32; i++) acc[i] = 0.f;
    fence_regs<32>(acc);
    const uint64_t bq = mkdesc(SB0 + WQ_OFF, 8192, 1024, 1);
    mbar_wait(bb + B_WQ, 0);
    {
      const uint64_t ad = mkdesc(SB0 + X_OFF + wg * 14336, 128, 1792, 0);
      #pragma unroll 1
      for (int j = 0; j < 4; j++) {
        mbar_wait(bb + B_X + 8 * (2 * j + wg), 0);
        WG_FENCE();
        #pragma unroll
        for (int ks = 0; ks < 7; ks++) mma_b64_tb(acc, ad + j * 1792 + ks * 16, bq + (j * 7 + ks) * 128, 1);
        WG_COMMIT();
      }
    }
    WG_WAIT(0); fence_regs<32>(acc);
    mbar_arrive_if(bb + B_MMA, (tid & 127) == 0);
    if (tid % 128 == 0) STAMPC(layer * 2, wg, 2);
    mbar_wait(bb + B_ST + 8 * wg, 0);
    mbar_wait(bb + B_CSQ, 0);
    if (tid % 128 == 0) STAMPC(layer * 2, wg, 3);
    const int r0 = wg * 64 + warp * 16 + g;
    const float mu0 = s_mean[r0], mu1 = s_mean[r0 + 8], rs0 = s_rstd[r0] * QSCALE, rs1 = s_rstd[r0 + 8] * QSCALE;
    float n0[2] = {0.f, 0.f}, n1[2] = {0.f, 0.f};
    #pragma unroll
    for (int j = 0; j < 7; j++) {
      const int n = 8 * j + 2 * c;
      const int h = (j < 3) ? 0 : (j > 3 ? 1 : (c >= 2 ? 1 : 0));
      const int d = n - 28 * h;
      const float2 cq = *(const float2*)(s_csq + n);
      const float* a = acc + 4 * j;
      const float q00 = (a[0] - mu0 * cq.x) * rs0, q01 = (a[1] - mu0 * cq.y) * rs0, q10 = (a[2] - mu1 * cq.x) * rs1, q11 = (a[3] - mu1 * cq.y) * rs1;
      const uint32_t h0 = pack_f16(q00, q01), h1 = pack_f16(q10, q11);
      uint8_t* qt = smem + Q_OFF + (h * 2 + wg) * 4096 + (warp * 2) * 512 + (d >> 3) * 128 + g * 16 + (d & 7) * 2;
      *(uint32_t*)qt = h0; *(uint32_t*)(qt + 512) = h1;
      bf16* qg = g_qb + ((size_t)(blockIdx.x * 4 + h * 2 + wg) * 64 + warp * 16 + g) * 32 + d;
      *(uint32_t*)qg = pack_bf16(q00, q01); *(uint32_t*)(qg + 8 * 32) = pack_bf16(q10, q11);
      const float2 f0 = __half22float2(*(const __half2*)&h0), f1 = __half22float2(*(const __half2*)&h1);
      const float e0 = fmaf(f0.x, f0.x, f0.y * f0.y), e1 = fmaf(f1.x, f1.x, f1.y * f1.y);
      if (j == 3) { n0[0] += h ? 0.f : e0; n1[0] += h ? 0.f : e1; n0[1] += h ? e0 : 0.f; n1[1] += h ? e1 : 0.f; }
      else { n0[j > 3] += e0; n1[j > 3] += e1; }
    }
    bool bad = false;
    #pragma unroll
    for (int h = 0; h < 2; h++) {
      n0[h] += __shfl_xor_sync(~0u, n0[h], 1); n0[h] += __shfl_xor_sync(~0u, n0[h], 2);
      n1[h] += __shfl_xor_sync(~0u, n1[h], 1); n1[h] += __shfl_xor_sync(~0u, n1[h], 2);
      if (c == 0) { s_qn[(h * 2 + wg) * 64 + warp * 16 + g] = n0[h]; s_qn[(h * 2 + wg) * 64 + warp * 16 + g + 8] = n1[h]; }
      bad |= !(n0[h] < 1e9f) || !(n1[h] < 1e9f);
    }
    if (bad) ((int*)s_misc)[4] = 1;
  } else if (wg == 2) {
    named_bar(5, 128); mbar_arrive_if(bb + B_CSQ, tid == 256);
    if (duty) {
      float acc[16];
      #pragma unroll
      for (int i = 0; i < 16; i++) acc[i] = 0.f;
      fence_regs<16>(acc);
      const uint64_t bk = mkdesc(SB0 + WKV_OFF, 512, 128, 0);
      {
        const uint64_t ad = mkdesc(SB0 + X_OFF + dh * 14336, 128, 1792, 0);
        mbar_wait(bb + B_WKV, 0);
        #pragma unroll 1
        for (int j = 0; j < 4; j++) {
          mbar_wait(bb + B_X + 8 * (2 * j + dh), 0);
          WG_FENCE();
          #pragma unroll
          for (int ks = 0; ks < 7; ks++) mma_b32_tb(acc, ad + j * 1792 + ks * 16, bk + (j * 7 + ks) * 64, 1);
          WG_COMMIT();
        }
      }
      WG_WAIT(0); fence_regs<16>(acc);
      if (tid % 128 == 0) STAMPC(layer * 2, wg, 2);
      mbar_wait(bb + B_ST + 8 * dh, 0);
      if (tid % 128 == 0) STAMPC(layer * 2, wg, 7);
      const int kind = r & 1, r0 = dh * 64 + warp * 16 + g;
      const float mu0 = s_mean[r0], mu1 = s_mean[r0 + 8], rs0 = s_rstd[r0], rs1 = s_rstd[r0 + 8];
      uint8_t* st = smem + KVS_OFF + (warp * 2) * 512 + g * 16 + c * 4;
      float n0 = 0.f, n1 = 0.f, am = 0.f;
      #pragma unroll
      for (int j = 0; j < 4; j++) {
        const float2 ck = *(const float2*)(s_cskv + 8 * j + 2 * c);
        const float* a = acc + 4 * j;
        float q00 = (a[0] - mu0 * ck.x) * rs0, q01 = (a[1] - mu0 * ck.y) * rs0, q10 = (a[2] - mu1 * ck.x) * rs1, q11 = (a[3] - mu1 * ck.y) * rs1;
        uint32_t h0 = pack_f16(q00, q01), h1 = pack_f16(q10, q11);
        const float2 f0 = __half22float2(*(const __half2*)&h0), f1 = __half22float2(*(const __half2*)&h1);
        n0 = fmaf(f0.x, f0.x, fmaf(f0.y, f0.y, n0)); n1 = fmaf(f1.x, f1.x, fmaf(f1.y, f1.y, n1));
        am = fmaxf(am, fmaxf(fmaxf(fabsf(q00), fabsf(q01)), fmaxf(fabsf(q10), fabsf(q11))));
        if (j == 3 && c == 2) { q00 = 1.f; q10 = 1.f; h0 = 0x00003C00u; h1 = 0x00003C00u; }
        *(uint32_t*)(st + j * 128) = h0; *(uint32_t*)(st + 512 + j * 128) = h1;
        *(uint32_t*)(st + 4096 + j * 128) = pack_bf16(q00, q01); *(uint32_t*)(st + 4096 + 512 + j * 128) = pack_bf16(q10, q11);
      }
      n0 += __shfl_xor_sync(~0u, n0, 1); n0 += __shfl_xor_sync(~0u, n0, 2);
      n1 += __shfl_xor_sync(~0u, n1, 1); n1 += __shfl_xor_sync(~0u, n1, 2);
      float nm = (n0 < 1e9f && n1 < 1e9f) ? fmaxf(n0, n1) : INFINITY;
      if (!(am < 1e30f)) am = INFINITY;
      nm = __uint_as_float(__reduce_max_sync(~0u, __float_as_uint(nm)));
      am = __uint_as_float(__reduce_max_sync(~0u, __float_as_uint(am)));
      float* s_red = s_misc + 8;
      if (lane == 0) { s_red[warp * 2] = nm; s_red[warp * 2 + 1] = am; }
      fence_async_smem();
      named_bar(5, 128);
      if (wid == 8 && elect_one()) {
        const size_t base = (size_t)t * TILE + kind * 8192 + dh * 4096;
        nm = fmaxf(fmaxf(s_red[0], s_red[2]), fmaxf(s_red[4], s_red[6]));
        am = fmaxf(fmaxf(s_red[1], s_red[3]), fmaxf(s_red[5], s_red[7]));
        *(float4*)(smem + KVS_OFF + 8192) = make_float4(nm, am, 0.f, 0.f);
        fence_async_smem();
        bulk_s2g(g_kvh + base, sb + KVS_OFF, 4096);
        bulk_s2g(&g_kvstat[kind * 32 + t * 2 + dh], sb + KVS_OFF + 8192, 16);
        bulk_s2g(g_kvb + base, sb + KVS_OFF + 4096, 4096);
        bulk_commit();
        STAMP(layer * 2, 2, 10);
        STAMPC(layer * 2, 2, 6);
        load_x(1 - dh);
        bulk_wait0();
        red_relaxed(&g_kvcnt[layer], 1);
        STAMP(layer * 2, 2, 13);
      }
    }
    if (tid % 128 == 0) STAMPC(layer * 2, wg, 3);
    mbar_arrive_if(bb + B_MMA, tid == 256);
  } else {
    {
      const int row = tid - 384;
      const float2* st = first ? g_st0 : g_st2;
      float sum = 0.f, sq = 0.f;
      #pragma unroll
      for (int s = 0; s < 8; s++) { const float2 p = st[(t * 8 + s) * 128 + row]; sum += p.x; sq += p.y; }
      const float mean = sum * (1.f / DM);
      s_mean[row] = mean; s_rstd[row] = rsqrtf(fmaxf(sq * (1.f / DM) - mean * mean, 0.f) + 1e-5f);
      mbar_arrive(bb + B_ST + 8 * (warp >> 1));
    }
    mbar_arrive_if(bb + B_MMA, lane == 0);
    if (tid % 128 == 0) STAMPC(layer * 2, wg, 2);
    if (warp == 0) {
      poll_ge_warp(&g_kvcnt[layer], 64);
      if (lane == 0) STAMP(layer * 2, 3, 12);
      mbar_wait(bb + B_MMA, 0);
      if (elect_one()) {
        fence_async_global();
        mbar_expect(bb + B_KV0, TILE); bulk_g2s(sb, g_kvh, TILE, bb + B_KV0);
        mbar_expect(bb + B_KV1, 3 * TILE); bulk_g2s(sb + TILE, g_kvh + TILE, 3 * TILE, bb + B_KV1);
        mbar_expect(bb + B_KV2, 8 * TILE); bulk_g2s(sb + 4 * TILE, g_kvh + 4 * TILE, 8 * TILE, bb + B_KV2);
      }
      __syncwarp();
      float2 ks, vs;
      asm volatile("ld.relaxed.gpu.global.v2.f32 {%0,%1}, [%2];" : "=f"(ks.x), "=f"(ks.y) : "l"(&g_kvstat[lane]) : "memory");
      asm volatile("ld.relaxed.gpu.global.v2.f32 {%0,%1}, [%2];" : "=f"(vs.x), "=f"(vs.y) : "l"(&g_kvstat[32 + lane]) : "memory");
      const float k2 = __uint_as_float(__reduce_max_sync(~0u, __float_as_uint(ks.x))), ka = __uint_as_float(__reduce_max_sync(~0u, __float_as_uint(ks.y)));
      const float va = __uint_as_float(__reduce_max_sync(~0u, __float_as_uint(vs.x < 1e9f ? vs.y : INFINITY)));
      if (lane == 0) {
        s_misc[0] = sqrt_fast(k2);
        const bool ok = (ka <= 30000.f) && (va <= 30000.f) && (ka >= 0.00390625f) && (va >= 0.00390625f) && (k2 < 1e9f);
        if (!ok) ((int*)s_misc)[4] = 1;
      }
    }
  }
  if (tid % 128 == 0) STAMPC(layer * 2, wg, 11);
  if (tid % 128 == 0) STAMPC(layer * 2, wg, 4);
  __syncthreads();
  if (tid % 128 == 0) STAMPC(layer * 2, wg, 5);

  float O[16];
  int slow;
  uint4 vA = make_uint4(0u, 0u, 0u, 0u), vB = vA;
  float c8[8] = {0.f, 0.f, 0.f, 0.f, 0.f, 0.f, 0.f, 0.f};
  {
    const int tw = tid % 128;
    if (tw < 64) {
      const float m = sqrt_fast(s_qn[wg * 64 + tw]) * s_misc[0] * 1.0005f + 0.01f;
      *(uint2*)(smem + Q_OFF + wg * 4096 + (tw / 8) * 512 + 3 * 128 + (tw % 8) * 16 + 8) = make_uint2(pack_f16(fmaxf(PSHIFT - m, -60000.f), 0.f), 0u);
      *(uint2*)(g_qb + ((size_t)(blockIdx.x * 4 + wg) * 64 + tw) * 32 + 28) = make_uint2(0u, 0u);
    }
    fence_async_smem();
    named_bar(1 + wg, 128);
    #pragma unroll
    for (int i = 0; i < 16; i++) O[i] = 0.f;
    fence_regs<16>(O);
    const uint64_t qd = mkdesc(SB0 + Q_OFF + wg * 4096, 128, 512, 0);
    const uint64_t kd0 = mkdesc(SB0, 128, 512, 0), vd0 = mkdesc(SB0 + 8192, 512, 128, 0);
    mbar_wait(bb + B_KV0, 0);
    if (tid % 128 == 0 && wg != 2) STAMPC(layer * 2, wg, 6);
    const int rb = blockIdx.x;
    const uint8_t* rt_src;
    uint8_t* rt_dst;
    {
      const int k = tid >> 2, cc = (rb < 56 ? 32 * rb : 32 * (rb - 56)) + 8 * (tid & 3);
      const int rr = cc / 224, wi = cc % 224, nt = wi / 112, ng = (wi % 112) / 8 + (rb < 56 ? 0 : 14);
      rt_src = (const uint8_t*)((rb < 56 ? wgate : wup) + cc + (size_t)k * DFF);
      rt_dst = g_w1t + (size_t)((rr * 2 + nt) * 14 + k / 32) * 14336 + ((k % 32) / 8) * 3584 + ng * 128 + (k % 8) * 16;
    }
    const uint8_t *rt_src2[2];
    uint8_t* rt_dst2[2];
    #pragma unroll
    for (int i = 0; i < 2; i++) {
      int idx = rb * 980 + tid + 512 * i;
      const bool dn = idx < 100352;
      if (!dn) idx -= 100352;
      const int k = idx / 56, ch = idx % 56, rs = ch / 7, ng2 = ch % 7;
      rt_src2[i] = (const uint8_t*)(dn ? wdown : wo) + (size_t)idx * 16;
      rt_dst2[i] = (dn ? g_w2t + (size_t)(rs * 16 + k / 112) * 12544 + ((k % 112) / 8) * 896 : g_wot + (size_t)rs * 50176 + (k / 8) * 896) + ng2 * 128 + (k % 8) * 16;
    }
    auto rt_ok = [&](int i) -> bool { return i < 4 ? (rb < 112 && (tid >> 2) + 128 * i < DM) : (tid + 512 * (i - 4) < 980); };
    auto rt_load = [&](int i, uint4& v) {
      const uint8_t* p = i < 4 ? rt_src + (size_t)i * (128 * DFF * 2) : (i == 4 ? rt_src2[0] : rt_src2[1]);
      asm volatile("{\n.reg .pred p;\nsetp.ne.b32 p, %5, 0;\nmov.b32 %0, 0;\nmov.b32 %1, 0;\nmov.b32 %2, 0;\nmov.b32 %3, 0;\n"
                   "@p ld.global.nc.v4.u32 {%0,%1,%2,%3}, [%4];\n}" : "=r"(v.x), "=r"(v.y), "=r"(v.z), "=r"(v.w) : "l"(p), "r"((int)rt_ok(i)));
    };
    auto rt_store = [&](int i, const uint4& v) {
      uint8_t* p = i < 4 ? rt_dst + i * (4 * 14336) : (i == 4 ? rt_dst2[0] : rt_dst2[1]);
      asm volatile("{\n.reg .pred p;\nsetp.ne.b32 p, %5, 0;\n@p st.global.v4.u32 [%0], {%1,%2,%3,%4};\n}"
                   :: "l"(p), "r"(v.x), "r"(v.y), "r"(v.z), "r"(v.w), "r"((int)rt_ok(i)) : "memory");
    };
    auto tile = [&](int jj) {
      const uint32_t cur = (jj < NST ? jj : jj - NST) * (TILE >> 4);
      if (((0x1012 >> jj) & 1) != 0) mbar_wait(bb + B_KV1 + 8 * ((jj >> 2) - (jj >> 3)), 0);
      if (jj == 8 && wid == 0) {
        mbar_wait(bb + B_EMPTY, 0);
        if (elect_one()) { mbar_expect(bb + B_KV3, 4 * TILE); bulk_g2s(sb, g_kvh + 12 * TILE, 4 * TILE, bb + B_KV3); }
      }
      #pragma unroll
      for (int h = 0; h < 2; h++) {
        uint32_t S[16], P[16];
        WG_FENCE();
        mma_qk_h64<0>(S, qd, kd0 + cur + h * 256); mma_qk_h64<1>(S, qd + 16, kd0 + cur + h * 256 + 16);
        WG_COMMIT();
        WG_WAIT(0); fence_regs<16>(S);
        if (h == 0 && jj == 4) mbar_arrive_if(bb + B_EMPTY, lane == 0);
        exp_part<0, 8>(S, P);
        WG_FENCE();
        mma_pv_h32<1>(O, P, vd0 + cur + h * 256); mma_pv_h32<1>(O, P + 4, vd0 + cur + h * 256 + 64);
        exp_part<8, 8>(S, P);
        WG_FENCE();
        mma_pv_h32<1>(O, P + 8, vd0 + cur + h * 256 + 128); mma_pv_h32<1>(O, P + 12, vd0 + cur + h * 256 + 192);
        WG_COMMIT();
      }
    };
    if (first) {
      int jv = lane >> 6;
      auto step = [&](uint4& v, int ju, int j) {
        if (ju >= 2) {
          rt_store(j - 2, v);
          if (ju < 6) {
            c8[0] += bf_lo(v.x); c8[1] += bf_hi(v.x); c8[2] += bf_lo(v.y); c8[3] += bf_hi(v.y);
            c8[4] += bf_lo(v.z); c8[5] += bf_hi(v.z); c8[6] += bf_lo(v.w); c8[7] += bf_hi(v.w);
          }
        }
        if (ju < 6) rt_load(j, v);
      };
      #pragma unroll 1
      for (int jj = 0; jj < 8; jj += 2, jv += 2) {
        step(vA, jj, jv); tile(jj);
        step(vB, jj + 1, jv + 1); tile(jj + 1);
      }
    }
    #pragma unroll 1
    for (int jj = first ? 8 : 0; jj < 16; jj++) tile(jj);
    WG_WAIT(0); fence_regs<16>(O);
    if (tid % 128 == 0 && wg != 2) STAMPC(layer * 2, wg, 7);
    const float l0 = __shfl_sync(~0u, O[12], (lane & ~3) | 2), l1 = __shfl_sync(~0u, O[14], (lane & ~3) | 2);
    const bool bad = !(l0 >= L_MIN && l0 < 1e30f) || !(l1 >= L_MIN && l1 < 1e30f) || ((volatile int*)s_misc)[4] != 0;
    slow = __syncthreads_or(bad);
  }
  if (slow) slow_path(G, smem, sb, wg, blockIdx.x);
  else write_O(G, O, t, r, wg);
  if (first) {
    #pragma unroll
    for (int e = 0; e < 8; e++) { c8[e] += __shfl_xor_sync(~0u, c8[e], 4); c8[e] += __shfl_xor_sync(~0u, c8[e], 8); c8[e] += __shfl_xor_sync(~0u, c8[e], 16); }
    float* s_p2 = (float*)(smem + SM2_OFF);
    if (lane < 4) {
      *(float4*)(s_p2 + wid * 32 + 8 * lane) = make_float4(c8[0], c8[1], c8[2], c8[3]);
      *(float4*)(s_p2 + wid * 32 + 8 * lane + 4) = make_float4(c8[4], c8[5], c8[6], c8[7]);
    }
    __syncthreads();
    if (wid == 4 && blockIdx.x < 112) {
      float sum = 0.f;
      #pragma unroll
      for (int w = 0; w < 16; w++) sum += s_p2[w * 32 + lane];
      g_cs[(blockIdx.x < 56 ? 32 * blockIdx.x : DFF + 32 * (blockIdx.x - 56)) + lane] = sum;
    }
  }
  if (tid % 128 == 0) { STAMPC(layer * 2, wg, 8); STAMP(layer * 2, wg, 14); }
}

namespace ffn {
constexpr int A_OFF = 0, RING_OFF = 114688, W1_STAGE = 14336, NS1 = 6, STG_OFF = RING_OFF + NS1 * W1_STAGE;
constexpr int STG_WG = 14336;
constexpr int SM_OFF = STG_OFF + 2 * STG_WG;
constexpr int BAR_OFF = SM_OFF;
constexpr int CS_OFF = SM_OFF + 448;
constexpr int SMEM = CS_OFF + 1792;
constexpr int HU = 28672, WU = 12544, NS2 = 5, NS2B = 4;
constexpr int B_O = 0, B_WO = 7, B_X1 = 8, B_FULL = 15, B_EMPTY = 21, B_WODONE = 27, B_F1DONE = 28, B_STAT = 29, B_SFULL = 30, B_SEMPTY = 32,
              B_FULL2 = 34, B_EMPTY2 = 39, B_FULLB = 44, B_EMPTYB = 48;
__device__ __forceinline__ uint32_t a2_off(int s) { return s * HU; }
__device__ __forceinline__ uint32_t b2_off(int s) { return NS2 * HU + s * WU; }
}

__global__ void __launch_bounds__(384, 1) ffn_kernel(uint8_t* __restrict__ G, const bf16* __restrict__ x0, bf16* __restrict__ out, int layer) {
  using namespace ffn;
  extern __shared__ __align__(1024) uint8_t smem[];
  const uint32_t sb = s2u(smem);
  const int tid = threadIdx.x, lane = tid % 32;
  const int b = blockIdx.x;
  const int t = 4 * (b / 32) + (b % 16) / 4, r = 4 * ((b / 16) % 2) + b % 4;
  const int wid = __shfl_sync(~0u, tid / 32, 0), wg = wid / 4;
  const uint32_t bb = sb + BAR_OFF;
  if (tid % 128 == 0) { STAMPC(layer * 2 + 1, wg, 0); STAMP(layer * 2 + 1, wg, 15); }
  if (tid == 0) {
    pdl_launch();
    #pragma unroll
    for (int i = 0; i < 52; i++) {
      int cnt = 1;
      if ((i >= B_EMPTY && i <= B_F1DONE) || (i >= B_EMPTY2 && i < B_FULLB) || i >= B_EMPTYB) cnt = 2;
      if (i == B_STAT) cnt = 64;
      if (i == B_SFULL || i == B_SFULL + 1) cnt = 128;
      mbar_init(bb + 8 * i, cnt);
    }
    asm volatile("fence.mbarrier_init.release.cluster;" ::: "memory");
  }

  if (wg == 2) {
    reg_dealloc<40>();
    named_bar(0, 384);
    const int pw = wid - 8;
    pdl_wait();
    if (pw == 0) {
      if (elect_one()) {
        if (b == 0) g_kvcnt[layer] = 0;
        mbar_wait(bb + 8 * B_WODONE, 0);
        int s = 0, ph = 1;
        #pragma unroll 1
        for (int it = 0; it < 28; it++) {
          mbar_wait(bb + 8 * (B_EMPTY + s), ph);
          mbar_expect(bb + 8 * (B_FULL + s), W1_STAGE);
          bulk_g2s(sb + RING_OFF + s * W1_STAGE, g_w1t + (size_t)(r * 28 + it) * W1_STAGE, W1_STAGE, bb + 8 * (B_FULL + s));
          if (++s == NS1) { s = 0; ph ^= 1; }
        }
        mbar_wait(bb + 8 * B_F1DONE, 0);
        s = 0; ph = 1;
        #pragma unroll 1
        for (int i = 0; i < 16; i++) {
          const int u = i < 8 ? 2 * i : (i == 8 ? 2 * r + 1 : 2 * ((i - 9) + (i - 9 >= r ? 1 : 0)) + 1);
          mbar_wait(bb + 8 * (B_EMPTYB + s), ph);
          mbar_expect(bb + 8 * (B_FULLB + s), WU);
          bulk_g2s(sb + b2_off(s), g_w2t + (size_t)(r * 16 + u) * WU, WU, bb + 8 * (B_FULLB + s));
          if (++s == NS2B) { s = 0; ph ^= 1; }
        }
      }
    } else if (pw == 1) {
      if (elect_one()) {
        #pragma unroll
        for (int j = 0; j < 4; j++) {
          mbar_expect(bb + 8 * (B_O + j), HU + WU);
          bulk_g2s(sb + RING_OFF + j * WU, g_wot + r * 50176 + j * WU, WU, bb + 8 * (B_O + j));
          bulk_g2s(sb + A_OFF + j * HU, g_O + (size_t)t * 114688 + j * HU, HU, bb + 8 * (B_O + j));
        }
      }
      mbar_wait(bb + 8 * B_WODONE, 0);
      poll_ge_warp(&g_x1cnt[layer][t], 2 * 8);
      if (elect_one()) {
        fence_async_global();
        #pragma unroll
        for (int j = 0; j < 4; j++) { mbar_expect(bb + 8 * (B_X1 + j), HU); bulk_g2s(sb + A_OFF + j * HU, g_x1 + (size_t)t * 114688 + j * HU, HU, bb + 8 * (B_X1 + j)); }
      }
      {
        const unsigned* hc = &g_hcnt[layer][t][0];
        #pragma unroll 1
        for (uint32_t it = 0; it < (1u << 21); it++) { if (__all_sync(~0u, ld_relaxed(hc + 2 * (lane & 7)) >= 2)) break; __nanosleep(200); }
        int s = 0, ph = 0;
        #pragma unroll 1
        for (int i = 0; i < 15; i++) {
          const int u = i < 8 ? 2 * i : 2 * ((i - 8) + (i - 8 >= r ? 1 : 0)) + 1;
          if (i == 8) {
            #pragma unroll 1
            for (uint32_t it = 0; it < (1u << 21); it++) { if (__all_sync(~0u, ld_relaxed(hc + 2 * (lane & 7) + 1) >= 2 || (lane & 7) == r)) break; }
          }
          mbar_wait(bb + 8 * (B_EMPTY2 + s), ph);
          if (elect_one()) {
            if (i == 0 || i == 8) fence_async_global();
            mbar_expect(bb + 8 * (B_FULL2 + s), HU);
            bulk_g2s(sb + a2_off(s), g_h + (size_t)(t * 16 + u) * HU, HU, bb + 8 * (B_FULL2 + s));
            STAMP2(2, i);
          }
          if (++s == NS2) { s = 0; ph ^= 1; }
        }
      }
    } else {
      const int i = tid - 320, w = pw - 2;
      float* s_cs = (float*)(smem + CS_OFF);
      #pragma unroll 1
      for (int j = i; j < 448; j += 64) {
        const int nt = j / 224, jj = j % 224;
        s_cs[j] = g_cs[(jj < 112 ? 0 : DFF - 112) + 224 * r + 112 * nt + jj];
      }
      mbar_arrive(bb + 8 * B_STAT);
      if (elect_one()) {
        #pragma unroll 1
        for (int nt = 0; nt < 2; nt++) {
          mbar_wait(bb + 8 * (B_SFULL + w), nt);
          STAMP2(3, w * 16 + nt * 4);
          bulk_s2g(g_h + (size_t)(t * 16 + 2 * r + nt) * HU + w * STG_WG, sb + STG_OFF + w * STG_WG, STG_WG);
          bulk_commit();
          bulk_wait0();
          STAMP2(3, w * 16 + nt * 4 + 1);
          mbar_arrive(bb + 8 * (B_SEMPTY + w));
          red_relaxed(&g_hcnt[layer][t][2 * r + nt], 1);
          STAMP2(3, w * 16 + nt * 4 + 2);
        }
      }
    }
  } else {
    named_bar(0, 384);
    reg_alloc<232>();
    const int warp = wid % 4, g = lane / 4, c = lane % 4, tw = tid % 128;
    const int row0 = wg * 64 + warp * 16 + g;
    const int grow0 = t * 128 + row0, col0 = 56 * r + 2 * c;
    uint32_t xr[14];
    pdl_wait();
    if (tw == 0) STAMPC(layer * 2 + 1, wg, 1);
    {
      #pragma unroll
      for (int j = 0; j < 7; j++) {
        if (layer == 0) {
          xr[2 * j] = __ldg((const uint32_t*)(x0 + (size_t)grow0 * DM + col0 + 8 * j));
          xr[2 * j + 1] = __ldg((const uint32_t*)(x0 + (size_t)(grow0 + 8) * DM + col0 + 8 * j));
        } else {
          const uint32_t o = tiled_off(grow0, col0 + 8 * j);
          xr[2 * j] = __ldg((const uint32_t*)(g_x2 + o)); xr[2 * j + 1] = __ldg((const uint32_t*)(g_x2 + o + 1792));
        }
      }
      float acc[28];
      #pragma unroll
      for (int i = 0; i < 28; i++) acc[i] = 0.f;
      fence_regs<28>(acc);
      const uint64_t ad = mkdesc(SB0 + A_OFF + wg * 14336, 128, 1792, 0), bd = mkdesc(SB0 + RING_OFF, 896, 128, 0);
      #pragma unroll 1
      for (int j = 0; j < 4; j++) {
        mbar_wait(bb + 8 * (B_O + j), 0);
        WG_FENCE();
        #pragma unroll
        for (int ks = 0; ks < 7; ks++) mma_b56_tb(acc, ad + j * 1792 + ks * 16, bd + (j * 7 + ks) * 112, 1);
        WG_COMMIT();
      }
      WG_WAIT(0); fence_regs<28>(acc);
      if (tw == 0) { mbar_arrive(bb + 8 * B_WODONE); STAMPC(layer * 2 + 1, wg, 2); }
      uint8_t* stg = smem + STG_OFF + wg * STG_WG;
      float s0 = 0.f, q0 = 0.f, s1 = 0.f, q1 = 0.f;
      #pragma unroll
      for (int j = 0; j < 7; j++) {
        const uint32_t a = pack_bf16(bf_lo(xr[2 * j]) + acc[4 * j], bf_hi(xr[2 * j]) + acc[4 * j + 1]);
        const uint32_t d = pack_bf16(bf_lo(xr[2 * j + 1]) + acc[4 * j + 2], bf_hi(xr[2 * j + 1]) + acc[4 * j + 3]);
        xr[2 * j] = a; xr[2 * j + 1] = d;
        *(uint32_t*)(stg + (warp * 2) * 896 + j * 128 + g * 16 + c * 4) = a;
        *(uint32_t*)(stg + (warp * 2 + 1) * 896 + j * 128 + g * 16 + c * 4) = d;
        s0 += bf_lo(a) + bf_hi(a); q0 = fmaf(bf_lo(a), bf_lo(a), fmaf(bf_hi(a), bf_hi(a), q0));
        s1 += bf_lo(d) + bf_hi(d); q1 = fmaf(bf_lo(d), bf_lo(d), fmaf(bf_hi(d), bf_hi(d), q1));
      }
      #pragma unroll
      for (int o = 1; o < 4; o <<= 1) { s0 += __shfl_xor_sync(~0u, s0, o); q0 += __shfl_xor_sync(~0u, q0, o); s1 += __shfl_xor_sync(~0u, s1, o); q1 += __shfl_xor_sync(~0u, q1, o); }
      if (c == 0) { *(float2*)(stg + 7168 + (warp * 16 + g) * 8) = make_float2(s0, q0); *(float2*)(stg + 7168 + (warp * 16 + g + 8) * 8) = make_float2(s1, q1); }
      fence_async_smem();
      named_bar(1 + wg, 128);
      if (warp == 0 && elect_one()) {
        const uint32_t sg = sb + STG_OFF + wg * STG_WG;
        uint8_t* dst = g_x1 + (size_t)t * 114688 + (r >> 1) * HU + (wg * 8) * 1792 + (r & 1) * 896;
        #pragma unroll
        for (int i = 0; i < 8; i++) bulk_s2g(dst + i * 1792, sg + i * 896, 896);
        bulk_s2g(&g_st1[(t * 8 + r) * 128 + wg * 64], sg + 7168, 512);
        bulk_commit();
        bulk_wait0();
        red_relaxed(&g_x1cnt[layer][t], 1);
      }
      if (tw == 0) STAMPC(layer * 2 + 1, wg, 3);
    }
    {
      const uint64_t ad = mkdesc(SB0 + A_OFF + wg * 14336, 128, 1792, 0), bd = mkdesc(SB0 + RING_OFF, 3584, 128, 0);
      const float* s_cs = (const float*)(smem + CS_OFF);
      float mu0 = 0.f, mu1 = 0.f, rs0 = 0.f, rs1 = 0.f;
      int s = 0, ph = 0;
      #pragma unroll 1
      for (int nt = 0; nt < 2; nt++) {
        float acc[112];
        #pragma unroll
        for (int i = 0; i < 112; i++) acc[i] = 0.f;
        fence_regs<112>(acc);
        #pragma unroll 1
        for (int kc = 0; kc < 14; kc++) {
          if (nt == 0) mbar_wait(bb + 8 * (B_X1 + (((2 * kc + 1) * 37) >> 8)), 0);
          if (nt == 0 && kc == 2) {
            const float2* sp = g_st1 + (t * 8 + 2 * c) * 128 + row0;
            const float2 p0 = __ldcg(sp), p1 = __ldcg(sp + 128), p2 = __ldcg(sp + 8), p3 = __ldcg(sp + 136);
            float s0 = p0.x + p1.x, q0 = p0.y + p1.y, s1 = p2.x + p3.x, q1 = p2.y + p3.y;
            #pragma unroll
            for (int o = 1; o < 4; o <<= 1) { s0 += __shfl_xor_sync(~0u, s0, o); q0 += __shfl_xor_sync(~0u, q0, o); s1 += __shfl_xor_sync(~0u, s1, o); q1 += __shfl_xor_sync(~0u, q1, o); }
            mu0 = s0 * (1.f / DM); mu1 = s1 * (1.f / DM);
            rs0 = rsqrtf(fmaxf(q0 * (1.f / DM) - mu0 * mu0, 0.f) + 1e-5f); rs1 = rsqrtf(fmaxf(q1 * (1.f / DM) - mu1 * mu1, 0.f) + 1e-5f);
          }
          mbar_wait(bb + 8 * (B_FULL + s), ph);
          if (kc == 0 && tw == 0) STAMPC(layer * 2 + 1, wg, 4 + 3 * nt);
          const int k0 = 2 * kc, k1 = 2 * kc + 1;
          const uint32_t u0 = (k0 * 37) >> 8, u1 = (k1 * 37) >> 8;
          const uint64_t a0 = ad + k0 * 16 + u0 * 1680, a1 = ad + k1 * 16 + u1 * 1680, w = bd + s * (W1_STAGE >> 4);
          WG_FENCE();
          mma_b224_tb(acc, a0, w, 1); mma_b224_tb(acc, a1, w + 448, 1);
          WG_COMMIT();
          if (kc > 0) {
            WG_WAIT(1);
            if (tw == 0) {
              mbar_arrive(bb + 8 * (B_EMPTY + (s == 0 ? NS1 - 1 : s - 1)));
              if (nt == 1 && (kc == 4 || kc == 7 || kc == 11)) mbar_arrive(bb + 8 * (B_EMPTY2 + (kc == 4 ? 0 : (kc == 7 ? 1 : 2))));
            }
          }
          if (++s == NS1) { s = 0; ph ^= 1; }
        }
        WG_WAIT(0); fence_regs<112>(acc);
        if (tw == 0) { mbar_arrive(bb + 8 * (B_EMPTY + (s == 0 ? NS1 - 1 : s - 1))); if (nt == 1) { mbar_arrive(bb + 8 * B_F1DONE); mbar_arrive(bb + 8 * (B_EMPTY2 + 3)); mbar_arrive(bb + 8 * (B_EMPTY2 + 4)); } STAMPC(layer * 2 + 1, wg, 5 + 3 * nt); }
        if (nt == 0) { mbar_wait(bb + 8 * B_STAT, 0); named_bar(1 + wg, 128); } else mbar_wait(bb + 8 * (B_SEMPTY + wg), 0);
        const float ka0 = 0.7978845608028654f * rs0, kb0 = 0.035677408136300125f * rs0 * rs0 * rs0, hh0 = 0.5f * rs0 * rs0;
        const float ka1 = 0.7978845608028654f * rs1, kb1 = 0.035677408136300125f * rs1 * rs1 * rs1, hh1 = 0.5f * rs1 * rs1;
        const uint32_t sta = sb + STG_OFF + wg * STG_WG + (warp * 2 + ((lane >> 3) & 1)) * 1792 + (lane >> 4) * 128 + (lane & 7) * 16;
        #pragma unroll
        for (int j2 = 0; j2 < 7; j2++) {
          uint32_t hp[4];
          #pragma unroll
          for (int jj = 0; jj < 2; jj++) {
            const int j = 2 * j2 + jj;
            const float2 cg = *(const float2*)(s_cs + 224 * nt + 8 * j + 2 * c), cu = *(const float2*)(s_cs + 224 * nt + 112 + 8 * j + 2 * c);
            float hv[4];
            #pragma unroll
            for (int e = 0; e < 4; e++) {
              const float mu = e < 2 ? mu0 : mu1, ka = e < 2 ? ka0 : ka1, kb = e < 2 ? kb0 : kb1, hh = e < 2 ? hh0 : hh1;
              const float tg = fmaf(-mu, (e & 1) ? cg.y : cg.x, acc[4 * j + e]);
              const float tu = fmaf(-mu, (e & 1) ? cu.y : cu.x, acc[56 + 4 * j + e]);
              const float th = tanhf_fast(tg * fmaf(kb, tg * tg, ka));
              const float p = tg * tu * hh;
              hv[e] = fmaf(p, th, p);
            }
            hp[2 * jj] = pack_bf16(hv[0], hv[1]); hp[2 * jj + 1] = pack_bf16(hv[2], hv[3]);
          }
          stmatrix_x4(sta + j2 * 256, hp[0], hp[1], hp[2], hp[3]);
        }
        fence_async_smem();
        mbar_arrive(bb + 8 * (B_SFULL + wg));
        if (nt == 1) named_bar(1 + wg, 128);
        if (tw == 0) STAMPC(layer * 2 + 1, wg, 6 + 3 * nt);
      }
    }
    {
      float acc[28];
      #pragma unroll
      for (int i = 0; i < 28; i++) acc[i] = 0.f;
      fence_regs<28>(acc);
      int s = 0, ph = 0, sB = 0, phB = 0;
      #pragma unroll 1
      for (int i = 0; i < 16; i++) {
        mbar_wait(bb + 8 * (B_FULLB + sB), phB);
        if (tw == 0) STAMP2(wg, 16 + i);
        if (i != 8) mbar_wait(bb + 8 * (B_FULL2 + s), ph);
        if (tw == 0) STAMP2(wg, i);
        if (tw == 0 && i == 0) STAMPC(layer * 2 + 1, wg, 10);
        if (tw == 0 && i == 8) STAMPC(layer * 2 + 1, wg, 11);
        const uint64_t a = mkdesc(SB0 + (i == 8 ? STG_OFF : a2_off(s)) + wg * 14336, 128, 1792, 0), w = mkdesc(SB0 + b2_off(sB), 896, 128, 0);
        WG_FENCE();
        #pragma unroll
        for (int ks = 0; ks < 7; ks++) mma_b56_tb(acc, a + ks * 16, w + ks * 112, 1);
        WG_COMMIT();
        if (i > 0) {
          WG_WAIT(1);
          if (tw == 0) {
            if (i != 9) mbar_arrive(bb + 8 * (B_EMPTY2 + (s == 0 ? NS2 - 1 : s - 1)));
            mbar_arrive(bb + 8 * (B_EMPTYB + (sB == 0 ? NS2B - 1 : sB - 1)));
          }
        }
        if (i != 8 && ++s == NS2) { s = 0; ph ^= 1; }
        if (++sB == NS2B) { sB = 0; phB ^= 1; }
      }
      WG_WAIT(0); fence_regs<28>(acc);
      if (tw == 0) STAMPC(layer * 2 + 1, wg, 12);
      float s0 = 0.f, q0 = 0.f, s1 = 0.f, q1 = 0.f;
      #pragma unroll
      for (int j = 0; j < 7; j++) {
        const uint32_t a = pack_bf16(bf_lo(xr[2 * j]) + acc[4 * j], bf_hi(xr[2 * j]) + acc[4 * j + 1]);
        const uint32_t d = pack_bf16(bf_lo(xr[2 * j + 1]) + acc[4 * j + 2], bf_hi(xr[2 * j + 1]) + acc[4 * j + 3]);
        if (layer == 0) {
          const uint32_t o = tiled_off(grow0, col0 + 8 * j);
          *(uint32_t*)(g_x2 + o) = a; *(uint32_t*)(g_x2 + o + 1792) = d;
        } else {
          *(uint32_t*)(out + (size_t)grow0 * DM + col0 + 8 * j) = a;
          *(uint32_t*)(out + (size_t)(grow0 + 8) * DM + col0 + 8 * j) = d;
        }
        s0 += bf_lo(a) + bf_hi(a); q0 = fmaf(bf_lo(a), bf_lo(a), fmaf(bf_hi(a), bf_hi(a), q0));
        s1 += bf_lo(d) + bf_hi(d); q1 = fmaf(bf_lo(d), bf_lo(d), fmaf(bf_hi(d), bf_hi(d), q1));
      }
      if (layer == 0) {
        #pragma unroll
        for (int o = 1; o < 4; o <<= 1) { s0 += __shfl_xor_sync(~0u, s0, o); q0 += __shfl_xor_sync(~0u, q0, o); s1 += __shfl_xor_sync(~0u, s1, o); q1 += __shfl_xor_sync(~0u, q1, o); }
        if (c == 0) { g_st2[(t * 8 + r) * 128 + row0] = make_float2(s0, q0); g_st2[(t * 8 + r) * 128 + row0 + 8] = make_float2(s1, q1); }
      }
      if (tw == 0) { STAMPC(layer * 2 + 1, wg, 13); STAMP(layer * 2 + 1, wg, 14); }
    }
  }
}
static_assert(ffn::SMEM <= 232448, "smem");
static_assert(attn::SMEM <= 232448, "smem");

#define PDL_A 1
#define PDL_F 0
extern "C" void kernel_launch(void* const* d_in, const int* in_sizes, int n_in, void* d_out, int out_size) {
  (void)in_sizes; (void)n_in; (void)out_size;
  const bf16* x = (const bf16*)d_in[0];
  const bf16* wq = (const bf16*)d_in[1];
  const bf16* wk = (const bf16*)d_in[2];
  const bf16* wv = (const bf16*)d_in[3];
  const bf16* wo = (const bf16*)d_in[4];
  const bf16* wgate = (const bf16*)d_in[6];
  const bf16* wup = (const bf16*)d_in[7];
  const bf16* wdown = (const bf16*)d_in[8];

  static uint8_t* G = nullptr;
  if (!G) {
    cudaGetSymbolAddress((void**)&G, g_scratch);
    cudaFuncSetAttribute(attn_kernel, cudaFuncAttributeMaxDynamicSharedMemorySize, attn::SMEM);
    cudaFuncSetAttribute(ffn_kernel, cudaFuncAttributeMaxDynamicSharedMemorySize, ffn::SMEM);
  }
  cudaLaunchAttribute pdl[1];
  pdl[0].id = cudaLaunchAttributeProgrammaticStreamSerialization;
  pdl[0].val.programmaticStreamSerializationAllowed = 1;
  cudaLaunchConfig_t cfg = {};
  cfg.stream = cudaStreamPerThread;
  cfg.gridDim = dim3(128); cfg.blockDim = dim3(512); cfg.dynamicSmemBytes = 0; cfg.attrs = pdl; cfg.numAttrs = 0;
  cudaLaunchKernelEx(&cfg, prep_kernel, G, x, wq, wk, wv);
#define NLAYERS 2
  for (int layer = 0; layer < NLAYERS; layer++) {
    cfg.gridDim = dim3(128); cfg.blockDim = dim3(512); cfg.dynamicSmemBytes = attn::SMEM;
    cfg.attrs = pdl; cfg.numAttrs = PDL_A ? 1 : 0;
    cudaLaunchKernelEx(&cfg, attn_kernel, G, wo, wgate, wup, wdown, layer);
    cfg.gridDim = dim3(128); cfg.blockDim = dim3(384); cfg.dynamicSmemBytes = ffn::SMEM;
    cfg.attrs = pdl; cfg.numAttrs = PDL_F ? 1 : 0;
    cudaLaunchKernelEx(&cfg, ffn_kernel, G, x, (bf16*)d_out, layer);
  }
}
```

```cpp
#include <cuda_runtime.h>
#include <cuda_bf16.h>
#include <cuda_fp16.h>
#include <cuda.h>
#include <stdint.h>

typedef __nv_bfloat16 bf16;

constexpr int SEQ = 2048, DM = 448, DFF = 1792;
constexpr float QSCALE = 0.18898223650461362f * 1.4426950408889634f;
constexpr float PSHIFT = 15.f;
constexpr float L_MIN = 128.f;

constexpr size_t O_KVH = 0;
constexpr size_t O_KVB = O_KVH + 16 * 16384;
constexpr size_t O_CNT = O_KVB + 16 * 16384;
constexpr size_t O_KVSTAT = O_CNT + 4096;
constexpr size_t O_CSQ = O_KVSTAT + 4096;
constexpr size_t O_CS = O_CSQ + 3072;
constexpr size_t O_ST1 = O_CS + 14336 + 2048;
constexpr size_t O_ST2 = O_ST1 + 131072;
constexpr size_t O_WQT = O_ST2 + 131072;
constexpr size_t O_WKVT = O_WQT + 8 * 57344;
constexpr size_t O_WOT = O_WKVT + 2 * 28672;
constexpr size_t O_W2T = O_WOT + 8 * 50176;
constexpr size_t O_W1T = O_W2T + 8 * 16 * 12544;
constexpr size_t O_O = O_W1T + 8 * 2 * 14 * 14336;
constexpr size_t O_X1 = O_O + SEQ * DM * 2;
constexpr size_t O_X2 = O_X1 + SEQ * DM * 2;
constexpr size_t O_H = O_X2 + SEQ * DM * 2;
constexpr size_t SCRATCH_BYTES = O_H + (size_t)SEQ * DFF * 2;
static_assert(O_ST1 % 1024 == 0 && O_WQT % 1024 == 0 && O_W1T % 128 == 0 && O_O % 128 == 0 && O_H % 128 == 0, "alignment");
__device__ __align__(1024) uint8_t g_scratch[SCRATCH_BYTES];
#define g_kvh (G + O_KVH)
#define g_kvb (G + O_KVB)
#define g_kvcnt ((unsigned*)(G + O_CNT))
#define g_x1cnt ((unsigned(*)[16])(G + O_CNT + 64))
#define g_hcnt ((unsigned(*)[16][16])(G + O_CNT + 256))
#define g_start ((unsigned*)(G + O_CNT + 2304))
#define g_role ((int*)(G + O_CNT + 2560))
#define g_kvstat ((float4*)(G + O_KVSTAT))
#define g_csq ((float*)(G + O_CSQ))
#define g_cs ((float*)(G + O_CS))
#define g_st1 ((float2*)(G + O_ST1))
#define g_st2 ((float2*)(G + O_ST2))
#define g_wqt (G + O_WQT)
#define g_wkvt (G + O_WKVT)
#define g_wot (G + O_WOT)
#define g_w2t (G + O_W2T)
#define g_w1t (G + O_W1T)
#define g_O (G + O_O)
#define g_x1 (G + O_X1)
#define g_x2 (G + O_X2)
#define g_h (G + O_H)

#define STAMP(kern, role, idx) do {} while (0)
#define STAMP2(role, idx) do {} while (0)
#define STAMPC(kern, role, idx) do {} while (0)
__device__ __forceinline__ uint32_t s2u(const void* p) { return (uint32_t)__cvta_generic_to_shared(p); }
__device__ __forceinline__ void mbar_init(uint32_t b, int c) { asm volatile("mbarrier.init.shared::cta.b64 [%0], %1;" :: "r"(b), "r"(c) : "memory"); }
__device__ __forceinline__ void mbar_expect(uint32_t b, uint32_t bytes) { asm volatile("mbarrier.arrive.expect_tx.shared::cta.b64 _, [%0], %1;" :: "r"(b), "r"(bytes) : "memory"); }
__device__ __forceinline__ void mbar_arrive(uint32_t b) { asm volatile("mbarrier.arrive.shared::cta.b64 _, [%0];" :: "r"(b) : "memory"); }
__device__ __forceinline__ void mbar_arrive_if(uint32_t b, bool p) {
  asm volatile("{\n.reg .pred q;\nsetp.ne.b32 q, %1, 0;\n@q mbarrier.arrive.shared::cta.b64 _, [%0];\n}" :: "r"(b), "r"((int)p) : "memory");
}
__device__ __forceinline__ void mbar_wait(uint32_t b, uint32_t ph) {
  asm volatile("{\n.reg .pred p;\n.reg .u32 n;\n"
               "mbarrier.try_wait.parity.shared::cta.b64 p, [%0], %1;\n@p bra MBW_DONE;\n"
               "mov.u32 n, 0;\n"
               "MBW_LOOP:\nmbarrier.try_wait.parity.shared::cta.b64 p, [%0], %1;\n@p bra MBW_DONE;\n"
               "add.u32 n, n, 1;\nsetp.lt.u32 p, n, 0x40000;\n@p bra MBW_LOOP;\n"
               "MBW_DONE:\n}" :: "r"(b), "r"(ph) : "memory");
}
__device__ __forceinline__ void bulk_g2s(uint32_t dst, const void* src, uint32_t bytes, uint32_t bar) {
  asm volatile("cp.async.bulk.shared::cluster.global.mbarrier::complete_tx::bytes [%0], [%1], %2, [%3];" :: "r"(dst), "l"(src), "r"(bytes), "r"(bar) : "memory");
}
__device__ __forceinline__ void bulk_s2g(void* dst, uint32_t src, uint32_t bytes) {
  asm volatile("cp.async.bulk.global.shared::cta.bulk_group [%0], [%1], %2;" :: "l"(dst), "r"(src), "r"(bytes) : "memory");
}
__device__ __forceinline__ void bulk_commit() { asm volatile("cp.async.bulk.commit_group;" ::: "memory"); }
__device__ __forceinline__ void bulk_wait0() { asm volatile("cp.async.bulk.wait_group 0;" ::: "memory"); }
__device__ __forceinline__ void bulk_wait0_read() { asm volatile("cp.async.bulk.wait_group.read 0;" ::: "memory"); }
__device__ __forceinline__ void prefetch_l2(const void* p, uint32_t bytes) { asm volatile("cp.async.bulk.prefetch.L2.global [%0], %1;" :: "l"(p), "r"(bytes) : "memory"); }
__device__ __forceinline__ void tma2d(uint32_t dst, const CUtensorMap* tm, int c0, int c1, uint32_t bar) {
  asm volatile("cp.async.bulk.tensor.2d.shared::cluster.global.mbarrier::complete_tx::bytes [%0], [%1, {%3, %4}], [%2];"
               :: "r"(dst), "l"(tm), "r"(bar), "r"(c0), "r"(c1) : "memory");
}
__device__ __forceinline__ void fence_async_smem() { asm volatile("fence.proxy.async.shared::cta;" ::: "memory"); }
__device__ __forceinline__ void fence_async_global() { asm volatile("fence.proxy.async.global;" ::: "memory"); }
__device__ __forceinline__ void named_bar(int id, int n) { asm volatile("bar.sync %0, %1;" :: "r"(id), "r"(n) : "memory"); }
__device__ __forceinline__ bool elect_one() {
  uint32_t p;
  asm volatile("{\n.reg .pred P;\nelect.sync _|P, 0xFFFFFFFF;\nselp.b32 %0, 1, 0, P;\n}" : "=r"(p));
  return p != 0;
}
constexpr int NSM = 132;
__device__ __forceinline__ int smid() { unsigned v; asm volatile("mov.u32 %0, %%smid;" : "=r"(v)); return (int)v; }
__device__ __forceinline__ void pdl_launch() { asm volatile("griddepcontrol.launch_dependents;" ::: "memory"); }
__device__ __forceinline__ void pdl_wait() { asm volatile("griddepcontrol.wait;" ::: "memory"); }
__device__ __forceinline__ void red_release(unsigned* p, unsigned v) { asm volatile("red.release.gpu.global.add.u32 [%0], %1;" :: "l"(p), "r"(v) : "memory"); }
__device__ __forceinline__ void red_relaxed(unsigned* p, unsigned v) { asm volatile("red.relaxed.gpu.global.add.u32 [%0], %1;" :: "l"(p), "r"(v) : "memory"); }
__device__ __forceinline__ unsigned ld_acquire(const unsigned* p) { unsigned v; asm volatile("ld.acquire.gpu.global.u32 %0, [%1];" : "=r"(v) : "l"(p) : "memory"); return v; }
__device__ __forceinline__ unsigned ld_relaxed(const unsigned* p) { unsigned v; asm volatile("ld.relaxed.gpu.global.u32 %0, [%1];" : "=r"(v) : "l"(p) : "memory"); return v; }
__device__ __forceinline__ uint32_t readback(const void* p) { uint32_t v; asm volatile("ld.relaxed.gpu.global.u32 %0, [%1];" : "=r"(v) : "l"(p) : "memory"); return v; }
__device__ __forceinline__ void fence_acquire() { asm volatile("fence.acquire.gpu;" ::: "memory"); }
__device__ __forceinline__ void poll_ge(const unsigned* p, unsigned target) {
  #pragma unroll 1
  for (uint32_t i = 0; i < (1u << 21); i++) { if (ld_relaxed(p) >= target) break; }
  fence_acquire();
}
__device__ __forceinline__ void poll_ge_warp(const unsigned* p, unsigned target) {
  #pragma unroll 1
  for (uint32_t i = 0; i < (1u << 21); i++) { if (__all_sync(~0u, ld_relaxed(p) >= target)) break; }
}
constexpr uint32_t SB0 = 1024;
__device__ __forceinline__ uint64_t mkdesc(uint32_t addr, uint32_t lbo, uint32_t sbo, uint32_t swz) {
  return (uint64_t)((addr & 0x3FFFF) >> 4) | ((uint64_t)(lbo >> 4) << 16) | ((uint64_t)(sbo >> 4) << 32) | ((uint64_t)swz << 62);
}
#define WG_FENCE() asm volatile("wgmma.fence.sync.aligned;" ::: "memory")
#define WG_COMMIT() asm volatile("wgmma.commit_group.sync.aligned;" ::: "memory")
#define WG_WAIT(n) asm volatile("wgmma.wait_group.sync.aligned %0;" :: "n"(n) : "memory")
template<int N> __device__ __forceinline__ void fence_regs(float* d) {
  #pragma unroll
  for (int i = 0; i < N; i++) asm volatile("" : "+f"(d[i]) :: "memory");
}
template<int N> __device__ __forceinline__ void fence_regs(uint32_t* d) {
  #pragma unroll
  for (int i = 0; i < N; i++) asm volatile("" : "+r"(d[i]) :: "memory");
}
template<int R> __device__ __forceinline__ void reg_alloc() { asm volatile("setmaxnreg.inc.sync.aligned.u32 %0;" :: "n"(R)); }
template<int R> __device__ __forceinline__ void reg_dealloc() { asm volatile("setmaxnreg.dec.sync.aligned.u32 %0;" :: "n"(R)); }
__device__ __forceinline__ float ex2f(float x) { float y; asm("ex2.approx.ftz.f32 %0, %1;" : "=f"(y) : "f"(x)); return y; }
__device__ __forceinline__ float sqrt_fast(float x) { float y; asm("sqrt.approx.f32 %0, %1;" : "=f"(y) : "f"(x)); return y; }
__device__ __forceinline__ float rcp_fast(float x) { float y; asm("rcp.approx.ftz.f32 %0, %1;" : "=f"(y) : "f"(x)); return y; }
__device__ __forceinline__ float tanhf_fast(float x) { float y; asm("tanh.approx.f32 %0, %1;" : "=f"(y) : "f"(x)); return y; }
__device__ __forceinline__ uint32_t pack_bf16(float lo, float hi) { uint32_t r; asm("cvt.rn.bf16x2.f32 %0, %1, %2;" : "=r"(r) : "f"(hi), "f"(lo)); return r; }
__device__ __forceinline__ uint32_t pack_f16(float lo, float hi) { uint32_t r; asm("cvt.rn.f16x2.f32 %0, %1, %2;" : "=r"(r) : "f"(hi), "f"(lo)); return r; }
__device__ __forceinline__ float bf_lo(uint32_t v) { return __uint_as_float(v << 16); }
__device__ __forceinline__ float bf_hi(uint32_t v) { return __uint_as_float(v & 0xFFFF0000u); }
__device__ __forceinline__ uint32_t hadd2(uint32_t a, uint32_t b) { uint32_t r; asm("add.rn.f16x2 %0, %1, %2;" : "=r"(r) : "r"(a), "r"(b)); return r; }
__device__ __forceinline__ uint32_t hsub2(uint32_t a, uint32_t b) { uint32_t r; asm("sub.rn.f16x2 %0, %1, %2;" : "=r"(r) : "r"(a), "r"(b)); return r; }
__device__ __forceinline__ uint32_t hfma2(uint32_t a, uint32_t b, uint32_t c) { uint32_t r; asm("fma.rn.f16x2 %0, %1, %2, %3;" : "=r"(r) : "r"(a), "r"(b), "r"(c)); return r; }
#define A_DEG 3
__device__ __forceinline__ uint32_t ex2_h2_poly(uint32_t x) {
  const uint32_t M = 0x66006600u;
  uint32_t t = hadd2(x, M);
  uint32_t j = hsub2(t, M);
  uint32_t f = hsub2(x, j);
  uint32_t p = hfma2(f, 0x2B102B10u, 0x33C333C3u);
  p = hfma2(p, f, 0x398C398Cu);
  p = hfma2(p, f, 0x3C003C00u);
  uint32_t sh;
  asm("shf.l.wrap.b32 %0, %1, %1, 10;" : "=r"(sh) : "r"(t));
  sh &= 0xFC00FC00u;
  return __viaddmax_s16x2(p, sh, 0);
}
__device__ __forceinline__ uint32_t ex2_h2_mufu(uint32_t x) { uint32_t y; asm("ex2.approx.f16x2 %0, %1;" : "=r"(y) : "r"(x)); return y; }
__device__ __forceinline__ void stmatrix_x4(uint32_t addr, uint32_t r0, uint32_t r1, uint32_t r2, uint32_t r3) {
  asm volatile("stmatrix.sync.aligned.m8n8.x4.shared.b16 [%0], {%1,%2,%3,%4};" :: "r"(addr), "r"(r0), "r"(r1), "r"(r2), "r"(r3) : "memory");
}
__device__ __forceinline__ uint4 ldg_nc128(const void* p) { uint4 v; asm volatile("ld.global.nc.v4.u32 {%0,%1,%2,%3}, [%4];" : "=r"(v.x), "=r"(v.y), "=r"(v.z), "=r"(v.w) : "l"(p)); return v; }
__device__ __forceinline__ uint32_t tiled_off(int row, int col) {
  return (row >> 7) * 114688 + (col / 112) * 28672 + ((row & 127) >> 3) * 1792 + ((col % 112) >> 3) * 128 + (row & 7) * 16 + (col & 7) * 2;
}
__device__ __forceinline__ uint2 ldg_nc64(const void* p) { uint2 v; asm volatile("ld.global.nc.v2.u32 {%0,%1}, [%2];" : "=r"(v.x), "=r"(v.y) : "l"(p)); return v; }

template<int SD> __device__ __forceinline__ void mma_qk_h64(uint32_t* d, uint64_t da, uint64_t db) {
  asm volatile("wgmma.mma_async.sync.aligned.m64n64k16.f16.f16.f16 {%0,%1,%2,%3,%4,%5,%6,%7,%8,%9,%10,%11,%12,%13,%14,%15}, %16, %17, %18, 1, 1, 0, 0;\n"
    : "+r"(d[0]),"+r"(d[1]),"+r"(d[2]),"+r"(d[3]),"+r"(d[4]),"+r"(d[5]),"+r"(d[6]),"+r"(d[7]),"+r"(d[8]),"+r"(d[9]),"+r"(d[10]),"+r"(d[11]),"+r"(d[12]),"+r"(d[13]),"+r"(d[14]),"+r"(d[15]) : "l"(da), "l"(db), "n"(SD));
}

template<int SD> __device__ __forceinline__ void mma_pv_h32(float* d, const uint32_t* a, uint64_t db) {
  asm volatile("wgmma.mma_async.sync.aligned.m64n32k16.f32.f16.f16 {%0,%1,%2,%3,%4,%5,%6,%7,%8,%9,%10,%11,%12,%13,%14,%15}, {%16,%17,%18,%19}, %20, %21, 1, 1, 1;\n"
    : "+f"(d[0]),"+f"(d[1]),"+f"(d[2]),"+f"(d[3]),"+f"(d[4]),"+f"(d[5]),"+f"(d[6]),"+f"(d[7]),"+f"(d[8]),"+f"(d[9]),"+f"(d[10]),"+f"(d[11]),"+f"(d[12]),"+f"(d[13]),"+f"(d[14]),"+f"(d[15]) : "r"(a[0]), "r"(a[1]), "r"(a[2]), "r"(a[3]), "l"(db), "n"(SD));
}

template<int SD> __device__ __forceinline__ void mma_qk_b64(float* d, const uint32_t* a, uint64_t db) {
  asm volatile("wgmma.mma_async.sync.aligned.m64n64k16.f32.bf16.bf16 {%0,%1,%2,%3,%4,%5,%6,%7,%8,%9,%10,%11,%12,%13,%14,%15,%16,%17,%18,%19,%20,%21,%22,%23,%24,%25,%26,%27,%28,%29,%30,%31}, {%32,%33,%34,%35}, %36, %37, 1, 1, 0;\n"
    : "+f"(d[0]),"+f"(d[1]),"+f"(d[2]),"+f"(d[3]),"+f"(d[4]),"+f"(d[5]),"+f"(d[6]),"+f"(d[7]),"+f"(d[8]),"+f"(d[9]),"+f"(d[10]),"+f"(d[11]),"+f"(d[12]),"+f"(d[13]),"+f"(d[14]),"+f"(d[15]),"+f"(d[16]),"+f"(d[17]),"+f"(d[18]),"+f"(d[19]),"+f"(d[20]),"+f"(d[21]),"+f"(d[22]),"+f"(d[23]),"+f"(d[24]),"+f"(d[25]),"+f"(d[26]),"+f"(d[27]),"+f"(d[28]),"+f"(d[29]),"+f"(d[30]),"+f"(d[31]) : "r"(a[0]), "r"(a[1]), "r"(a[2]), "r"(a[3]), "l"(db), "n"(SD));
}

template<int SD> __device__ __forceinline__ void mma_pv_b32(float* d, const uint32_t* a, uint64_t db) {
  asm volatile("wgmma.mma_async.sync.aligned.m64n32k16.f32.bf16.bf16 {%0,%1,%2,%3,%4,%5,%6,%7,%8,%9,%10,%11,%12,%13,%14,%15}, {%16,%17,%18,%19}, %20, %21, 1, 1, 1;\n"
    : "+f"(d[0]),"+f"(d[1]),"+f"(d[2]),"+f"(d[3]),"+f"(d[4]),"+f"(d[5]),"+f"(d[6]),"+f"(d[7]),"+f"(d[8]),"+f"(d[9]),"+f"(d[10]),"+f"(d[11]),"+f"(d[12]),"+f"(d[13]),"+f"(d[14]),"+f"(d[15]) : "r"(a[0]), "r"(a[1]), "r"(a[2]), "r"(a[3]), "l"(db), "n"(SD));
}

__device__ __forceinline__ void mma_b64_tb(float* d, uint64_t da, uint64_t db, int sd) {
  asm volatile("{\n.reg .pred p;\nsetp.ne.b32 p, %34, 0;\n"
    "wgmma.mma_async.sync.aligned.m64n64k16.f32.bf16.bf16 {%0,%1,%2,%3,%4,%5,%6,%7,%8,%9,%10,%11,%12,%13,%14,%15,%16,%17,%18,%19,%20,%21,%22,%23,%24,%25,%26,%27,%28,%29,%30,%31}, %32, %33, p, 1, 1, 0, 1;\n}\n"
    : "+f"(d[0]),"+f"(d[1]),"+f"(d[2]),"+f"(d[3]),"+f"(d[4]),"+f"(d[5]),"+f"(d[6]),"+f"(d[7]),"+f"(d[8]),"+f"(d[9]),"+f"(d[10]),"+f"(d[11]),"+f"(d[12]),"+f"(d[13]),"+f"(d[14]),"+f"(d[15]),"+f"(d[16]),"+f"(d[17]),"+f"(d[18]),"+f"(d[19]),"+f"(d[20]),"+f"(d[21]),"+f"(d[22]),"+f"(d[23]),"+f"(d[24]),"+f"(d[25]),"+f"(d[26]),"+f"(d[27]),"+f"(d[28]),"+f"(d[29]),"+f"(d[30]),"+f"(d[31]) : "l"(da), "l"(db), "r"(sd));
}

__device__ __forceinline__ void mma_b32_tb(float* d, uint64_t da, uint64_t db, int sd) {
  asm volatile("{\n.reg .pred p;\nsetp.ne.b32 p, %18, 0;\n"
    "wgmma.mma_async.sync.aligned.m64n32k16.f32.bf16.bf16 {%0,%1,%2,%3,%4,%5,%6,%7,%8,%9,%10,%11,%12,%13,%14,%15}, %16, %17, p, 1, 1, 0, 1;\n}\n"
    : "+f"(d[0]),"+f"(d[1]),"+f"(d[2]),"+f"(d[3]),"+f"(d[4]),"+f"(d[5]),"+f"(d[6]),"+f"(d[7]),"+f"(d[8]),"+f"(d[9]),"+f"(d[10]),"+f"(d[11]),"+f"(d[12]),"+f"(d[13]),"+f"(d[14]),"+f"(d[15]) : "l"(da), "l"(db), "r"(sd));
}

__device__ __forceinline__ void mma_b224_tb(float* d, uint64_t da, uint64_t db, int sd) {
  asm volatile("{\n.reg .pred p;\nsetp.ne.b32 p, %114, 0;\n"
    "wgmma.mma_async.sync.aligned.m64n224k16.f32.bf16.bf16 {%0,%1,%2,%3,%4,%5,%6,%7,%8,%9,%10,%11,%12,%13,%14,%15,%16,%17,%18,%19,%20,%21,%22,%23,%24,%25,%26,%27,%28,%29,%30,%31,%32,%33,%34,%35,%36,%37,%38,%39,%40,%41,%42,%43,%44,%45,%46,%47,%48,%49,%50,%51,%52,%53,%54,%55,%56,%57,%58,%59,%60,%61,%62,%63,%64,%65,%66,%67,%68,%69,%70,%71,%72,%73,%74,%75,%76,%77,%78,%79,%80,%81,%82,%83,%84,%85,%86,%87,%88,%89,%90,%91,%92,%93,%94,%95,%96,%97,%98,%99,%100,%101,%102,%103,%104,%105,%106,%107,%108,%109,%110,%111}, %112, %113, p, 1, 1, 0, 1;\n}\n"
    : "+f"(d[0]),"+f"(d[1]),"+f"(d[2]),"+f"(d[3]),"+f"(d[4]),"+f"(d[5]),"+f"(d[6]),"+f"(d[7]),"+f"(d[8]),"+f"(d[9]),"+f"(d[10]),"+f"(d[11]),"+f"(d[12]),"+f"(d[13]),"+f"(d[14]),"+f"(d[15]),"+f"(d[16]),"+f"(d[17]),"+f"(d[18]),"+f"(d[19]),"+f"(d[20]),"+f"(d[21]),"+f"(d[22]),"+f"(d[23]),"+f"(d[24]),"+f"(d[25]),"+f"(d[26]),"+f"(d[27]),"+f"(d[28]),"+f"(d[29]),"+f"(d[30]),"+f"(d[31]),"+f"(d[32]),"+f"(d[33]),"+f"(d[34]),"+f"(d[35]),"+f"(d[36]),"+f"(d[37]),"+f"(d[38]),"+f"(d[39]),"+f"(d[40]),"+f"(d[41]),"+f"(d[42]),"+f"(d[43]),"+f"(d[44]),"+f"(d[45]),"+f"(d[46]),"+f"(d[47]),"+f"(d[48]),"+f"(d[49]),"+f"(d[50]),"+f"(d[51]),"+f"(d[52]),"+f"(d[53]),"+f"(d[54]),"+f"(d[55]),"+f"(d[56]),"+f"(d[57]),"+f"(d[58]),"+f"(d[59]),"+f"(d[60]),"+f"(d[61]),"+f"(d[62]),"+f"(d[63]),"+f"(d[64]),"+f"(d[65]),"+f"(d[66]),"+f"(d[67]),"+f"(d[68]),"+f"(d[69]),"+f"(d[70]),"+f"(d[71]),"+f"(d[72]),"+f"(d[73]),"+f"(d[74]),"+f"(d[75]),"+f"(d[76]),"+f"(d[77]),"+f"(d[78]),"+f"(d[79]),"+f"(d[80]),"+f"(d[81]),"+f"(d[82]),"+f"(d[83]),"+f"(d[84]),"+f"(d[85]),"+f"(d[86]),"+f"(d[87]),"+f"(d[88]),"+f"(d[89]),"+f"(d[90]),"+f"(d[91]),"+f"(d[92]),"+f"(d[93]),"+f"(d[94]),"+f"(d[95]),"+f"(d[96]),"+f"(d[97]),"+f"(d[98]),"+f"(d[99]),"+f"(d[100]),"+f"(d[101]),"+f"(d[102]),"+f"(d[103]),"+f"(d[104]),"+f"(d[105]),"+f"(d[106]),"+f"(d[107]),"+f"(d[108]),"+f"(d[109]),"+f"(d[110]),"+f"(d[111]) : "l"(da), "l"(db), "r"(sd));
}

__device__ __forceinline__ void mma_b56_tb(float* d, uint64_t da, uint64_t db, int sd) {
  asm volatile("{\n.reg .pred p;\nsetp.ne.b32 p, %30, 0;\n"
    "wgmma.mma_async.sync.aligned.m64n56k16.f32.bf16.bf16 {%0,%1,%2,%3,%4,%5,%6,%7,%8,%9,%10,%11,%12,%13,%14,%15,%16,%17,%18,%19,%20,%21,%22,%23,%24,%25,%26,%27}, %28, %29, p, 1, 1, 0, 1;\n}\n"
    : "+f"(d[0]),"+f"(d[1]),"+f"(d[2]),"+f"(d[3]),"+f"(d[4]),"+f"(d[5]),"+f"(d[6]),"+f"(d[7]),"+f"(d[8]),"+f"(d[9]),"+f"(d[10]),"+f"(d[11]),"+f"(d[12]),"+f"(d[13]),"+f"(d[14]),"+f"(d[15]),"+f"(d[16]),"+f"(d[17]),"+f"(d[18]),"+f"(d[19]),"+f"(d[20]),"+f"(d[21]),"+f"(d[22]),"+f"(d[23]),"+f"(d[24]),"+f"(d[25]),"+f"(d[26]),"+f"(d[27]) : "l"(da), "l"(db), "r"(sd));
}

namespace attn {
constexpr int TILE = 16384, NST = 12;
constexpr int X_OFF = 0, WQ_OFF = 114688, WKV_OFF = 172032;
constexpr int SCR_OFF = NST * TILE;
constexpr int Q_OFF = SCR_OFF + 16384;
constexpr int SM_OFF = Q_OFF + 16384;
constexpr int BAR_OFF = SM_OFF;
constexpr int MEAN_OFF = SM_OFF + 224;
constexpr int RSTD_OFF = MEAN_OFF + 512;
constexpr int CSQ_OFF = RSTD_OFF + 512;
constexpr int CSKV_OFF = CSQ_OFF + 256;
constexpr int QN_OFF = CSKV_OFF + 128;
constexpr int MISC_OFF = QN_OFF + 1024;
constexpr int SMEM = MISC_OFF + 64;
constexpr int RAW_OFF = 200704;
constexpr int PART_OFF = 225792;
constexpr int KVS_OFF = 200704;
constexpr int SM2_OFF = 209152;
constexpr int B_X = 0  , B_KV0 = 112, B_KV1 = 120, B_KV2 = 128, B_KV3 = 136, B_EMPTY = 144, B_WQ = 152, B_SLOW = 160,
              B_WKV = 168, B_ST = 176  , B_CSQ = 192, B_MMA = 200, B_PART = 208;
#define A_PAT 0x5555
#define A_STRUCT 1
constexpr uint32_t PAT = A_PAT;

template<int I0, int N> __device__ __forceinline__ void exp_part(const uint32_t* s, uint32_t* p) {
  #pragma unroll
  for (int i = I0; i < I0 + N; i++) p[i] = ((PAT >> i) & 1) ? ex2_h2_poly(s[i]) : ex2_h2_mufu(s[i]);
}
__device__ __forceinline__ void exp_block(const uint32_t* s, uint32_t* p) { exp_part<0, 16>(s, p); }

__device__ __forceinline__ void write_O(uint8_t* __restrict__ G, const float* O, int t, int r, int wg) {
  const int lane = threadIdx.x % 32, warp = (threadIdx.x % 128) / 32, g = lane / 4, c = lane % 4;
  const float l0 = __shfl_sync(~0u, O[12], (lane & ~3) | 2), l1 = __shfl_sync(~0u, O[14], (lane & ~3) | 2);
  const float i0 = rcp_fast(l0), i1 = rcp_fast(l1);
  const int tok = t * 128 + (wg & 1) * 64 + warp * 16 + g, col = 56 * r + 28 * (wg >> 1) + 2 * c;
  #pragma unroll
  for (int j = 0; j < 4; j++) {
    if (j < 3 || c < 2) {
      const uint32_t o = tiled_off(tok, col + 8 * j);
      *(uint32_t*)(g_O + o) = pack_bf16(O[4 * j] * i0, O[4 * j + 1] * i0);
      *(uint32_t*)(g_O + o + 1792) = pack_bf16(O[4 * j + 2] * i1, O[4 * j + 3] * i1);
    }
  }
}

__device__ __forceinline__ void mma16816(float* d, const uint32_t* a, uint32_t b0, uint32_t b1) {
  asm volatile("mma.sync.aligned.m16n8k16.row.col.f32.bf16.bf16.f32 {%0,%1,%2,%3}, {%4,%5,%6,%7}, {%8,%9}, {%0,%1,%2,%3};"
               : "+f"(d[0]), "+f"(d[1]), "+f"(d[2]), "+f"(d[3]) : "r"(a[0]), "r"(a[1]), "r"(a[2]), "r"(a[3]), "r"(b0), "r"(b1));
}
__device__ __forceinline__ void slow_path(uint8_t* __restrict__ G, const bf16* __restrict__ x0, const bf16* __restrict__ wq, int layer,
                                          const uint8_t* smem, uint32_t sb, int wg, int cta) {
  const int lane = threadIdx.x % 32, warp = (threadIdx.x % 128) / 32, g = lane / 4, c = lane % 4;
  const uint32_t bar = sb + BAR_OFF + B_SLOW;
  if (threadIdx.x == 0) fence_async_global();
  uint32_t q[2][4];
  {
    const int t = cta / 8, r = cta % 8, hcol = 56 * r + 28 * (wg >> 1), row = (wg & 1) * 64 + warp * 16 + g;
    const float* s_mean = (const float*)(smem + MEAN_OFF); const float* s_rstd = (const float*)(smem + RSTD_OFF); const float* s_csq = (const float*)(smem + CSQ_OFF);
    #pragma unroll 1
    for (int i = 0; i < 8; i++) {
      const int ks = i >> 2, rr = row + 8 * (i & 1), d = ks * 16 + 2 * c + 8 * ((i >> 1) & 1);
      float a0 = 0.f, a1 = 0.f;
      if (d < 28) {
        #pragma unroll 4
        for (int k = 0; k < DM; k++) {
          const float xv = __bfloat162float(layer == 0 ? x0[(size_t)(t * 128 + rr) * DM + k] : *(const bf16*)(g_x2 + tiled_off(t * 128 + rr, k)));
          const uint32_t w = *(const uint32_t*)(wq + (size_t)k * DM + hcol + d);
          a0 = fmaf(xv, bf_lo(w), a0); a1 = fmaf(xv, bf_hi(w), a1);
        }
        const float mu = s_mean[rr], rs = s_rstd[rr] * QSCALE;
        a0 = (a0 - mu * s_csq[28 * (wg >> 1) + d]) * rs; a1 = (a1 - mu * s_csq[28 * (wg >> 1) + d + 1]) * rs;
      }
      const uint32_t v = pack_bf16(a0, a1);
      #pragma unroll
      for (int z = 0; z < 8; z++) if (z == i) q[z >> 2][z & 3] = v;
    }
  }
  float O[16];
  #pragma unroll
  for (int i = 0; i < 16; i++) O[i] = 0.f;
  float m0 = -INFINITY, m1 = -INFINITY;
  #pragma unroll 1
  for (int j = 0; j < 16; j++) {
    __syncthreads();
    if (threadIdx.x == 0) { mbar_expect(bar, TILE); bulk_g2s(sb, g_kvb + (size_t)j * TILE, TILE, bar); }
    mbar_wait(bar, j & 1);
    #pragma unroll 1
    for (int kb = 0; kb < 8; kb++) {
      float S[8] = {0.f, 0.f, 0.f, 0.f, 0.f, 0.f, 0.f, 0.f};
      #pragma unroll
      for (int nb = 0; nb < 2; nb++) {
        const uint8_t* kp = smem + (2 * kb + nb) * 512 + g * 16 + c * 4;
        mma16816(S + 4 * nb, q[0], *(const uint32_t*)kp, *(const uint32_t*)(kp + 128));
        mma16816(S + 4 * nb, q[1], *(const uint32_t*)(kp + 256), *(const uint32_t*)(kp + 384));
      }
      float x0 = fmaxf(fmaxf(S[0], S[1]), fmaxf(S[4], S[5])), x1 = fmaxf(fmaxf(S[2], S[3]), fmaxf(S[6], S[7]));
      x0 = fmaxf(x0, __shfl_xor_sync(~0u, x0, 1)); x0 = fmaxf(x0, __shfl_xor_sync(~0u, x0, 2));
      x1 = fmaxf(x1, __shfl_xor_sync(~0u, x1, 1)); x1 = fmaxf(x1, __shfl_xor_sync(~0u, x1, 2));
      const float n0 = fmaxf(m0, x0), n1 = fmaxf(m1, x1);
      const float a0 = (m0 == n0) ? 1.f : exp2f(m0 - n0), a1 = (m1 == n1) ? 1.f : exp2f(m1 - n1);
      m0 = n0; m1 = n1;
      uint32_t P[4];
      P[0] = pack_bf16(exp2f(S[0] - m0), exp2f(S[1] - m0)); P[1] = pack_bf16(exp2f(S[2] - m1), exp2f(S[3] - m1));
      P[2] = pack_bf16(exp2f(S[4] - m0), exp2f(S[5] - m0)); P[3] = pack_bf16(exp2f(S[6] - m1), exp2f(S[7] - m1));
      #pragma unroll
      for (int nb = 0; nb < 4; nb++) {
        O[4 * nb] *= a0; O[4 * nb + 1] *= a0; O[4 * nb + 2] *= a1; O[4 * nb + 3] *= a1;
        uint32_t b0, b1;
        asm volatile("ldmatrix.sync.aligned.m8n8.x2.trans.shared.b16 {%0,%1}, [%2];" : "=r"(b0), "=r"(b1)
                     : "r"(sb + 8192 + (2 * kb + ((lane >> 3) & 1)) * 512 + nb * 128 + (lane & 7) * 16));
        mma16816(O + 4 * nb, P, b0, b1);
      }
    }
  }
  write_O(G, O, cta / 8, cta % 8, wg);
}
}

#define PID cta
__global__ void __launch_bounds__(512, 1) attn_kernel(const __grid_constant__ CUtensorMap tm_x, const __grid_constant__ CUtensorMap tm_wq, uint8_t* __restrict__ G,
                                                      const bf16* __restrict__ x0, const bf16* __restrict__ wq, const bf16* __restrict__ wk, const bf16* __restrict__ wv, const bf16* __restrict__ wo,
                                                      const bf16* __restrict__ wgate, const bf16* __restrict__ wup, const bf16* __restrict__ wdown,
                                                      int layer, int use_role) {
  using namespace attn;
  extern __shared__ __align__(1024) uint8_t smem[];
  const uint32_t sb = s2u(smem);
  const int tid = threadIdx.x, lane = tid % 32, wid = __shfl_sync(~0u, tid / 32, 0);
  const int wg = wid / 4, warp = wid % 4, g = lane / 4, c = lane % 4;
  const bool first = layer == 0;
  int cta = blockIdx.x;
  if (use_role) {
    if (first) {
      if (tid == 448) { g_role[smid()] = cta < 128 ? cta : -1; __threadfence(); pdl_launch(); }
      if (cta >= 128) return;
    } else {
      cta = __shfl_sync(~0u, (int)ld_relaxed((const unsigned*)&g_role[smid()]), 0);
      if (tid == 448) red_relaxed(&g_start[2], 1);
      if (cta < 0) {
        if (tid == 0) { pdl_launch(); poll_ge(&g_start[2], NSM); }
        return;
      }
    }
  }
  const int t = cta / 8, r = cta % 8;
  const uint32_t bb = sb + BAR_OFF;
  float* s_mean = (float*)(smem + MEAN_OFF);
  float* s_rstd = (float*)(smem + RSTD_OFF);
  float* s_csq = (float*)(smem + CSQ_OFF);
  float* s_cskv = (float*)(smem + CSKV_OFF);
  float* s_qn = (float*)(smem + QN_OFF);
  float* s_misc = (float*)(smem + MISC_OFF);
  if (tid % 128 == 0) { STAMPC(layer * 2, wg, 0); STAMP(layer * 2, wg, 15); }

  if (first && tid == 480) { asm volatile("prefetch.tensormap [%0];" :: "l"(&tm_x) : "memory"); asm volatile("prefetch.tensormap [%0];" :: "l"(&tm_wq) : "memory"); }
  const bool duty = r < 4;
  const int dh = duty ? (r >> 1) : 0;
  auto load_x = [&](int h) {
    if (first) {
      #pragma unroll
      for (int j = 0; j < 7; j++) { mbar_expect(bb + B_X + 8 * (2 * j + h), 8192); tma2d(sb + X_OFF + j * 16384 + h * 8192, &tm_x, 64 * j, 128 * t + 64 * h, bb + B_X + 8 * (2 * j + h)); }
    } else {
      const uint8_t* xs = g_x2 + (size_t)t * 114688 + h * 14336;
      #pragma unroll
      for (int j = 0; j < 4; j++) { mbar_expect(bb + B_X + 8 * (2 * j + h), 14336); bulk_g2s(sb + X_OFF + j * 28672 + h * 14336, xs + j * 28672, 14336, bb + B_X + 8 * (2 * j + h)); }
    }
  };
  if (first) {
    const uint8_t* pf = nullptr;
    if (tid < 112) pf = (const uint8_t*)x0 + (size_t)cta * 14336 + tid * 128;
    else if (tid < 112 + 25) pf = (const uint8_t*)wq + (size_t)cta * 3136 + (tid - 112) * 128;
    else if (tid < 112 + 25 + 2) pf = (const uint8_t*)wk + (size_t)min((int)cta * 2 + (tid - 137), 195) * 128;
    else if (tid < 112 + 25 + 4) pf = (const uint8_t*)wv + (size_t)min((int)cta * 2 + (tid - 139), 195) * 128;
    if (pf) asm volatile("prefetch.global.L2 [%0];" :: "l"(pf));
  }
  if (wid == 15 && elect_one()) {
    #pragma unroll
    for (int i = 0; i < 27; i++) mbar_init(bb + 8 * i, (i == 18 || i == 26) ? 16 : ((i == 22 || i == 23) ? 64 : (i == 25 ? 7 : (i == 24 ? 2 : 1))));
    asm volatile("fence.mbarrier_init.release.cluster;" ::: "memory");
    ((int*)s_misc)[4] = 0;
  }
  __syncthreads();
  if (wid == 15 && elect_one()) {
    if (!(first && use_role)) pdl_launch();
    if (first) {
      if (duty) { mbar_expect(bb + B_WKV, 25088); bulk_g2s(sb + RAW_OFF, (r & 1) ? wv : wk, 25088, bb + B_WKV); }
      load_x(dh);
      mbar_expect(bb + B_WQ, 57344);
      tma2d(sb + WQ_OFF, &tm_wq, 56 * r, 0, bb + B_WQ); tma2d(sb + WQ_OFF + 28672, &tm_wq, 56 * r, 224, bb + B_WQ);
      load_x(1 - dh);
    } else {
      if (duty) { mbar_expect(bb + B_WKV, 28672); bulk_g2s(sb + WKV_OFF, g_wkvt + (r & 1) * 28672, 28672, bb + B_WKV); }
      pdl_wait();
      load_x(dh);
      mbar_expect(bb + B_WQ, 57344); bulk_g2s(sb + WQ_OFF, g_wqt + r * 57344, 57344, bb + B_WQ);
      load_x(1 - dh);
    }
  }
  if (tid % 128 == 0) STAMPC(layer * 2, wg, 9);
  float kacc[16];
  #pragma unroll
  for (int i = 0; i < 16; i++) kacc[i] = 0.f;
  fence_regs<16>(kacc);
  const uint64_t bk = mkdesc(SB0 + WKV_OFF, 512, 128, 0);
  if (first) {
    float* s_part = (float*)(smem + PART_OFF);
    if (duty) {
      const int uk = lane % 8;
      float ck[4] = {0.f, 0.f, 0.f, 0.f};
      mbar_wait(bb + B_WKV, 0);
      #pragma unroll
      for (int i = 0; i < 7; i++) {
        const int k = wid * 28 + 4 * i + lane / 8;
        uint2 v = make_uint2(0u, 0u);
        if (uk < 7) v = *(const uint2*)(smem + RAW_OFF + k * 56 + uk * 8);
        *(uint2*)(smem + WKV_OFF + (k / 8) * 512 + (uk / 2) * 128 + (k % 8) * 16 + (uk % 2) * 8) = v;
        ck[0] += bf_lo(v.x); ck[1] += bf_hi(v.x); ck[2] += bf_lo(v.y); ck[3] += bf_hi(v.y);
      }
      #pragma unroll
      for (int e = 0; e < 4; e++) { ck[e] += __shfl_xor_sync(~0u, ck[e], 8); ck[e] += __shfl_xor_sync(~0u, ck[e], 16); }
      if (lane < 8) *(float4*)(s_part + wid * 32 + 4 * lane) = make_float4(ck[0], ck[1], ck[2], ck[3]);
      fence_async_smem();
      __syncthreads();
    }
    if (tid % 128 == 0) STAMPC(layer * 2, wg, 10);
    {
      const int row = dh * 64 + (tid >> 3), ch = tid & 7;
      const uint64_t ad = mkdesc(SB0 + X_OFF + dh * 8192, 16, 1024, 1);
      float s0 = 0.f, s1 = 0.f, q0 = 0.f, q1 = 0.f;
      auto stat_step = [&](int j) {
        const uint4 v = *(const uint4*)(smem + X_OFF + j * 16384 + row * 128 + ((ch ^ (row & 7)) * 16));
        const uint32_t w[4] = {v.x, v.y, v.z, v.w};
        #pragma unroll
        for (int e = 0; e < 4; e++) { const float a = bf_lo(w[e]), b = bf_hi(w[e]); s0 += a; s1 += b; q0 = fmaf(a, a, q0); q1 = fmaf(b, b, q1); }
      };
      if (wg == 2 && duty) {
        #pragma unroll 1
        for (int j = 0; j < 7; j++) {
          mbar_wait(bb + B_X + 8 * (2 * j + dh), 0);
          WG_FENCE();
          #pragma unroll
          for (int ks = 0; ks < 4; ks++) mma_b32_tb(kacc, ad + j * 1024 + ks * 2, bk + (j * 4 + ks) * 64, 1);
          WG_COMMIT();
          stat_step(j);
        }
        WG_WAIT(0); fence_regs<16>(kacc);
      } else {
        #pragma unroll 1
        for (int j = 0; j < 7; j++) {
          mbar_wait(bb + B_X + 8 * (2 * j + dh), 0);
          stat_step(j);
        }
      }
      float sum = s0 + s1, sq = q0 + q1;
      #pragma unroll
      for (int o = 1; o < 8; o <<= 1) { sum += __shfl_xor_sync(~0u, sum, o); sq += __shfl_xor_sync(~0u, sq, o); }
      if (ch == 0) {
        const float mean = sum * (1.f / DM);
        s_mean[row] = mean; s_rstd[row] = rsqrtf(fmaxf(sq * (1.f / DM) - mean * mean, 0.f) + 1e-5f);
        mbar_arrive(bb + B_ST + 8 * dh);
      }
    }
    if (duty) {
      if (wid == 15 && t == 0 && r < 2 && elect_one()) { bulk_s2g(g_wkvt + r * 28672, sb + WKV_OFF, 28672); bulk_commit(); }
      if (wid == 9) {
        float sum = 0.f;
        #pragma unroll
        for (int w = 0; w < 16; w++) sum += s_part[w * 32 + lane];
        s_cskv[lane] = sum;
        if (t == 0 && r < 2) g_csq[512 + r * 32 + lane] = sum;
      }
    }
    if (wg == 1 - dh) {
      const int idx = tid & 127, row = (1 - dh) * 64 + (idx >> 1), ch = (idx & 1) * 4;
      float s0 = 0.f, s1 = 0.f, q0 = 0.f, q1 = 0.f;
      #pragma unroll 1
      for (int j = 0; j < 7; j++) {
        mbar_wait(bb + B_X + 8 * (2 * j + 1 - dh), 0);
        #pragma unroll
        for (int u = 0; u < 4; u++) {
          const uint4 v = *(const uint4*)(smem + X_OFF + j * 16384 + row * 128 + (((ch + u) ^ (row & 7)) * 16));
          const uint32_t w[4] = {v.x, v.y, v.z, v.w};
          #pragma unroll
          for (int e = 0; e < 4; e++) { const float a = bf_lo(w[e]), b = bf_hi(w[e]); s0 += a; s1 += b; q0 = fmaf(a, a, q0); q1 = fmaf(b, b, q1); }
        }
      }
      float sum = s0 + s1, sq = q0 + q1;
      sum += __shfl_xor_sync(~0u, sum, 1); sq += __shfl_xor_sync(~0u, sq, 1);
      if ((idx & 1) == 0) {
        const float mean = sum * (1.f / DM);
        s_mean[row] = mean; s_rstd[row] = rsqrtf(fmaxf(sq * (1.f / DM) - mean * mean, 0.f) + 1e-5f);
        mbar_arrive(bb + B_ST + 8 * (1 - dh));
      }
    }
  } else {
    pdl_wait();
    if (wg == 2) {
      if (warp < 2) s_csq[tid - 256] = g_csq[r * 64 + tid - 256];
      else if (warp == 2 && duty) s_cskv[lane] = g_csq[512 + (r & 1) * 32 + lane];
    }
  }
  if (tid % 128 == 0) STAMPC(layer * 2, wg, 1);
  if (cta == 127 && tid >= 128 && tid < 128 + 272) {
    const int i = tid - 128;
    if (i < 256) (&g_hcnt[layer][0][0])[i] = 0; else g_x1cnt[layer][i - 256] = 0;
    if (i == 0) g_start[first ? 3 : 1] = 0;
  }

  if (wg < 2) {
    float acc[32];
    #pragma unroll
    for (int i = 0; i < 32; i++) acc[i] = 0.f;
    fence_regs<32>(acc);
    const uint64_t bq = mkdesc(SB0 + WQ_OFF, 8192, 1024, 1);
    mbar_wait(bb + B_WQ, 0);
    if (first) {
      const uint64_t ad = mkdesc(SB0 + X_OFF + wg * 8192, 16, 1024, 1);
      #pragma unroll 1
      for (int j = 0; j < 7; j++) {
        mbar_wait(bb + B_X + 8 * (2 * j + wg), 0);
        WG_FENCE();
        #pragma unroll
        for (int ks = 0; ks < 4; ks++) mma_b64_tb(acc, ad + j * 1024 + ks * 2, bq + (j * 4 + ks) * 128, 1);
        WG_COMMIT();
      }
    } else {
      const uint64_t ad = mkdesc(SB0 + X_OFF + wg * 14336, 128, 1792, 0);
      #pragma unroll 1
      for (int j = 0; j < 4; j++) {
        mbar_wait(bb + B_X + 8 * (2 * j + wg), 0);
        WG_FENCE();
        #pragma unroll
        for (int ks = 0; ks < 7; ks++) mma_b64_tb(acc, ad + j * 1792 + ks * 16, bq + (j * 7 + ks) * 128, 1);
        WG_COMMIT();
      }
    }
    WG_WAIT(0); fence_regs<32>(acc);
    mbar_arrive_if(bb + B_MMA, (tid & 127) == 0);
    if (tid % 128 == 0) STAMPC(layer * 2, wg, 2);
    mbar_wait(bb + B_ST + 8 * wg, 0);
    mbar_wait(bb + B_CSQ, 0);
    if (tid % 128 == 0) STAMPC(layer * 2, wg, 3);
    const int r0 = wg * 64 + warp * 16 + g;
    const float mu0 = s_mean[r0], mu1 = s_mean[r0 + 8], rs0 = s_rstd[r0] * QSCALE, rs1 = s_rstd[r0 + 8] * QSCALE;
    float n0[2] = {0.f, 0.f}, n1[2] = {0.f, 0.f};
    #pragma unroll
    for (int j = 0; j < 7; j++) {
      const int n = 8 * j + 2 * c;
      const int h = (j < 3) ? 0 : (j > 3 ? 1 : (c >= 2 ? 1 : 0));
      const int d = n - 28 * h;
      const float2 cq = *(const float2*)(s_csq + n);
      const float* a = acc + 4 * j;
      const float q00 = (a[0] - mu0 * cq.x) * rs0, q01 = (a[1] - mu0 * cq.y) * rs0, q10 = (a[2] - mu1 * cq.x) * rs1, q11 = (a[3] - mu1 * cq.y) * rs1;
      const uint32_t h0 = pack_f16(q00, q01), h1 = pack_f16(q10, q11);
      uint8_t* qt = smem + Q_OFF + (h * 2 + wg) * 4096 + (warp * 2) * 512 + (d >> 3) * 128 + g * 16 + (d & 7) * 2;
      *(uint32_t*)qt = h0; *(uint32_t*)(qt + 512) = h1;
      const float e0 = fmaf(q00, q00, q01 * q01), e1 = fmaf(q10, q10, q11 * q11);
      if (j == 3) { n0[0] += h ? 0.f : e0; n1[0] += h ? 0.f : e1; n0[1] += h ? e0 : 0.f; n1[1] += h ? e1 : 0.f; }
      else { n0[j > 3] += e0; n1[j > 3] += e1; }
    }
    bool bad = false;
    #pragma unroll
    for (int h = 0; h < 2; h++) {
      n0[h] += __shfl_xor_sync(~0u, n0[h], 1); n0[h] += __shfl_xor_sync(~0u, n0[h], 2);
      n1[h] += __shfl_xor_sync(~0u, n1[h], 1); n1[h] += __shfl_xor_sync(~0u, n1[h], 2);
      if (c == 0) { s_qn[(h * 2 + wg) * 64 + warp * 16 + g] = n0[h]; s_qn[(h * 2 + wg) * 64 + warp * 16 + g + 8] = n1[h]; }
      bad |= !(n0[h] < 1e9f) || !(n1[h] < 1e9f);
    }
    if (bad) ((int*)s_misc)[4] = 1;
  } else if (wg == 2) {
    named_bar(5, 128);
    if (!first) mbar_arrive_if(bb + B_CSQ, tid == 256 || tid == 288);
    if (duty) {
      float* acc = kacc;
      if (!first) {
        const uint64_t ad = mkdesc(SB0 + X_OFF + dh * 14336, 128, 1792, 0);
        mbar_wait(bb + B_WKV, 0);
        #pragma unroll 1
        for (int j = 0; j < 4; j++) {
          mbar_wait(bb + B_X + 8 * (2 * j + dh), 0);
          WG_FENCE();
          #pragma unroll
          for (int ks = 0; ks < 7; ks++) mma_b32_tb(acc, ad + j * 1792 + ks * 16, bk + (j * 7 + ks) * 64, 1);
          WG_COMMIT();
        }
      }
      WG_WAIT(0); fence_regs<16>(acc);
      if (tid % 128 == 0) STAMPC(layer * 2, wg, 2);
      mbar_wait(bb + B_ST + 8 * dh, 0);
      if (tid % 128 == 0) STAMPC(layer * 2, wg, 7);
      const int kind = r & 1, r0 = dh * 64 + warp * 16 + g;
      const float mu0 = s_mean[r0], mu1 = s_mean[r0 + 8], rs0 = s_rstd[r0], rs1 = s_rstd[r0 + 8];
      const size_t base = (size_t)t * TILE + kind * 8192 + (dh * 8 + warp * 2) * 512 + g * 16 + c * 4;
      float n0 = 0.f, n1 = 0.f, am = 0.f;
      #pragma unroll
      for (int j = 0; j < 4; j++) {
        const float2 ck = *(const float2*)(s_cskv + 8 * j + 2 * c);
        const float* a = acc + 4 * j;
        float q00 = (a[0] - mu0 * ck.x) * rs0, q01 = (a[1] - mu0 * ck.y) * rs0, q10 = (a[2] - mu1 * ck.x) * rs1, q11 = (a[3] - mu1 * ck.y) * rs1;
        uint32_t h0 = pack_f16(q00, q01), h1 = pack_f16(q10, q11);
        n0 = fmaf(q00, q00, fmaf(q01, q01, n0)); n1 = fmaf(q10, q10, fmaf(q11, q11, n1));
        am = fmaxf(am, fmaxf(fmaxf(fabsf(q00), fabsf(q01)), fmaxf(fabsf(q10), fabsf(q11))));
        if (j == 3 && c == 2) { q00 = 1.f; q10 = 1.f; h0 = 0x00003C00u; h1 = 0x00003C00u; }
        *(uint32_t*)(g_kvh + base + j * 128) = h0; *(uint32_t*)(g_kvh + base + 512 + j * 128) = h1;
        *(uint32_t*)(g_kvb + base + j * 128) = pack_bf16(q00, q01); *(uint32_t*)(g_kvb + base + 512 + j * 128) = pack_bf16(q10, q11);
      }
      uint32_t rb = 0;
      #pragma unroll
      for (int j = 0; j < 4; j++)
        rb ^= readback(g_kvh + base + j * 128) ^ readback(g_kvh + base + 512 + j * 128) ^ readback(g_kvb + base + j * 128) ^ readback(g_kvb + base + 512 + j * 128);
      n0 += __shfl_xor_sync(~0u, n0, 1); n0 += __shfl_xor_sync(~0u, n0, 2);
      n1 += __shfl_xor_sync(~0u, n1, 1); n1 += __shfl_xor_sync(~0u, n1, 2);
      float nm = (n0 < 1e9f && n1 < 1e9f) ? fmaxf(n0, n1) : INFINITY;
      if (!(am < 1e30f)) am = INFINITY;
      nm = __uint_as_float(__reduce_max_sync(~0u, __float_as_uint(nm)));
      am = __uint_as_float(__reduce_max_sync(~0u, __float_as_uint(am)));
      if (lane == 0) {
        float4* ps = &g_kvstat[(kind * 32 + t * 2 + dh) * 4 + warp];
        *ps = make_float4(nm, am, 0.f, 0.f);
        rb ^= readback(ps);
      }
      asm volatile("" :: "r"(rb) : "memory");
      if (tid % 128 == 0) { STAMP(layer * 2, 2, 10); STAMPC(layer * 2, 2, 6); }
      named_bar(5, 128);
      if (tid == 256) { red_relaxed(&g_kvcnt[layer], 1); STAMP(layer * 2, 2, 13); }
    }
    if (tid % 128 == 0) STAMPC(layer * 2, wg, 3);
    mbar_arrive_if(bb + B_MMA, tid == 256);
  } else {
    if (!first) {
      const int row = tid - 384;
      float sum = 0.f, sq = 0.f;
      #pragma unroll
      for (int s = 0; s < 8; s++) { const float2 p = g_st2[(t * 8 + s) * 128 + row]; sum += p.x; sq += p.y; }
      const float mean = sum * (1.f / DM);
      s_mean[row] = mean; s_rstd[row] = rsqrtf(fmaxf(sq * (1.f / DM) - mean * mean, 0.f) + 1e-5f);
      mbar_arrive(bb + B_ST + 8 * (warp >> 1));
    }
    if (first) {
      float* s_wp = (float*)(smem + RAW_OFF);
      const int ch = lane & 7;
      float c8[8] = {0.f, 0.f, 0.f, 0.f, 0.f, 0.f, 0.f, 0.f};
      mbar_wait(bb + B_WQ, 0);
      #pragma unroll 7
      for (int i = 0; i < 28; i++) {
        const int k = warp * 4 + (lane >> 3) + 16 * i;
        const uint4 v = *(const uint4*)(smem + WQ_OFF + k * 128 + ((ch ^ (k & 7)) * 16));
        c8[0] += bf_lo(v.x); c8[1] += bf_hi(v.x); c8[2] += bf_lo(v.y); c8[3] += bf_hi(v.y);
        c8[4] += bf_lo(v.z); c8[5] += bf_hi(v.z); c8[6] += bf_lo(v.w); c8[7] += bf_hi(v.w);
      }
      #pragma unroll
      for (int e = 0; e < 8; e++) { c8[e] += __shfl_xor_sync(~0u, c8[e], 8); c8[e] += __shfl_xor_sync(~0u, c8[e], 16); }
      if (lane < 8) {
        *(float4*)(s_wp + warp * 64 + 8 * lane) = make_float4(c8[0], c8[1], c8[2], c8[3]);
        *(float4*)(s_wp + warp * 64 + 8 * lane + 4) = make_float4(c8[4], c8[5], c8[6], c8[7]);
      }
      named_bar(6, 128);
      if (warp < 2) {
        const int n = tid - 384;
        const float sum = s_wp[n] + s_wp[64 + n] + s_wp[128 + n] + s_wp[192 + n];
        s_csq[n] = sum;
        if (t == 0) g_csq[r * 64 + n] = sum;
        __syncwarp();
        mbar_arrive_if(bb + B_CSQ, lane == 0);
      }
    }
    if (first && warp == 3) bulk_wait0_read();
    __syncwarp();
    mbar_arrive_if(bb + B_MMA, lane == 0);
    if (tid % 128 == 0) STAMPC(layer * 2, wg, 2);
    if (warp == 0) {
      poll_ge_warp(&g_kvcnt[layer], 64);
      if (lane == 0) STAMP(layer * 2, 3, 12);
      mbar_wait(bb + B_MMA, 0);
      if (elect_one()) {
        fence_async_global();
        mbar_expect(bb + B_KV0, TILE); bulk_g2s(sb, g_kvh, TILE, bb + B_KV0);
        mbar_expect(bb + B_KV1, 3 * TILE); bulk_g2s(sb + TILE, g_kvh + TILE, 3 * TILE, bb + B_KV1);
        mbar_expect(bb + B_KV2, 8 * TILE); bulk_g2s(sb + 4 * TILE, g_kvh + 4 * TILE, 8 * TILE, bb + B_KV2);
      }
      __syncwarp();
      float k2 = 0.f, ka = 0.f, va = 0.f;
      #pragma unroll
      for (int i = 0; i < 4; i++) {
        float2 ks, vs;
        asm volatile("ld.relaxed.gpu.global.v2.f32 {%0,%1}, [%2];" : "=f"(ks.x), "=f"(ks.y) : "l"(&g_kvstat[lane + 32 * i]) : "memory");
        asm volatile("ld.relaxed.gpu.global.v2.f32 {%0,%1}, [%2];" : "=f"(vs.x), "=f"(vs.y) : "l"(&g_kvstat[128 + lane + 32 * i]) : "memory");
        k2 = fmaxf(k2, ks.x); ka = fmaxf(ka, ks.y); va = fmaxf(va, vs.x < 1e9f ? vs.y : INFINITY);
      }
      k2 = __uint_as_float(__reduce_max_sync(~0u, __float_as_uint(k2))); ka = __uint_as_float(__reduce_max_sync(~0u, __float_as_uint(ka)));
      va = __uint_as_float(__reduce_max_sync(~0u, __float_as_uint(va)));
      if (lane == 0) {
        s_misc[0] = sqrt_fast(k2);
        const bool ok = (ka <= 30000.f) && (va <= 30000.f) && (ka >= 0.00390625f) && (va >= 0.00390625f) && (k2 < 1e9f);
        if (!ok) ((int*)s_misc)[4] = 1;
      }
    }
  }
  if (tid % 128 == 0) STAMPC(layer * 2, wg, 11);
  if (tid % 128 == 0) STAMPC(layer * 2, wg, 4);
  __syncthreads();
  if (tid % 128 == 0) STAMPC(layer * 2, wg, 5);

  float O[16];
  int slow;
  uint4 vA = make_uint4(0u, 0u, 0u, 0u), vB = vA;
  float c8[8] = {0.f, 0.f, 0.f, 0.f, 0.f, 0.f, 0.f, 0.f};
  {
    const int tw = tid % 128;
    if (tw < 64) {
      const float m = sqrt_fast(s_qn[wg * 64 + tw]) * s_misc[0] * 1.002f + 0.01f;
      *(uint2*)(smem + Q_OFF + wg * 4096 + (tw / 8) * 512 + 3 * 128 + (tw % 8) * 16 + 8) = make_uint2(pack_f16(fmaxf(PSHIFT - m, -60000.f), 0.f), 0u);
    }
    fence_async_smem();
    named_bar(1 + wg, 128);
    #pragma unroll
    for (int i = 0; i < 16; i++) O[i] = 0.f;
    fence_regs<16>(O);
    const uint64_t qd = mkdesc(SB0 + Q_OFF + wg * 4096, 128, 512, 0);
    const uint64_t kd0 = mkdesc(SB0, 128, 512, 0), vd0 = mkdesc(SB0 + 8192, 512, 128, 0);
    mbar_wait(bb + B_KV0, 0);
    if (tid % 128 == 0 && wg != 2) STAMPC(layer * 2, wg, 6);
    const int rb = cta;
    const uint8_t* rt_src = nullptr;
    uint8_t* rt_dst = nullptr;
    const uint8_t* rt_src2[3] = {nullptr, nullptr, nullptr};
    uint8_t* rt_dst2[3] = {nullptr, nullptr, nullptr};
    bool rt_ok3 = false;
    if (first) {
      const int k = tid >> 2, cc = (rb < 56 ? 32 * rb : 32 * (rb - 56)) + 8 * (tid & 3);
      const int rr = cc / 224, wi = cc % 224, nt = wi / 112, ng = (wi % 112) / 8 + (rb < 56 ? 0 : 14);
      rt_src = (const uint8_t*)((rb < 56 ? wgate : wup) + cc + (size_t)k * DFF);
      rt_dst = g_w1t + (size_t)((rr * 2 + nt) * 14 + k / 32) * 14336 + ((k % 32) / 8) * 3584 + ng * 128 + (k % 8) * 16;
      #pragma unroll
      for (int i = 0; i < 2; i++) {
        int idx = rb * 980 + tid + 512 * i;
        const bool dn = idx < 100352;
        if (!dn) idx -= 100352;
        const int k2 = idx / 56, ch = idx % 56, rs = ch / 7, ng2 = ch % 7;
        rt_src2[i] = (const uint8_t*)(dn ? wdown : wo) + (size_t)idx * 16;
        rt_dst2[i] = (dn ? g_w2t + (size_t)(rs * 16 + k2 / 112) * 12544 + ((k2 % 112) / 8) * 896 : g_wot + (size_t)rs * 50176 + (k2 / 8) * 896) + ng2 * 128 + (k2 % 8) * 16;
      }
      {
        const int idx = rb * 224 + tid, rs = idx / 3584, kq = (idx % 3584) >> 3, ch = idx & 7;
        rt_ok3 = tid < 224;
        rt_src2[2] = (56 * rs + 8 * ch < DM) ? (const uint8_t*)(wq + (size_t)kq * DM + 56 * rs + 8 * ch) : nullptr;
        rt_dst2[2] = g_wqt + rs * 57344 + kq * 128 + ((ch ^ (kq & 7)) * 16);
      }
    }
    auto rt_ok = [&](int i) -> bool { return i < 4 ? (rb < 112 && (tid >> 2) + 128 * i < DM) : (i < 6 ? (tid + 512 * (i - 4) < 980) : rt_ok3); };
    auto rt_load = [&](int i, uint4& v) {
      const uint8_t* p = i < 4 ? rt_src + (size_t)i * (128 * DFF * 2) : (i == 4 ? rt_src2[0] : (i == 5 ? rt_src2[1] : rt_src2[2]));
      asm volatile("{\n.reg .pred p;\nsetp.ne.b32 p, %5, 0;\nmov.b32 %0, 0;\nmov.b32 %1, 0;\nmov.b32 %2, 0;\nmov.b32 %3, 0;\n"
                   "@p ld.global.nc.v4.u32 {%0,%1,%2,%3}, [%4];\n}" : "=r"(v.x), "=r"(v.y), "=r"(v.z), "=r"(v.w) : "l"(p), "r"((int)(rt_ok(i) && p != nullptr)));
    };
    auto rt_store = [&](int i, const uint4& v) {
      uint8_t* p = i < 4 ? rt_dst + i * (4 * 14336) : (i == 4 ? rt_dst2[0] : (i == 5 ? rt_dst2[1] : rt_dst2[2]));
      asm volatile("{\n.reg .pred p;\nsetp.ne.b32 p, %5, 0;\n@p st.global.v4.u32 [%0], {%1,%2,%3,%4};\n}"
                   :: "l"(p), "r"(v.x), "r"(v.y), "r"(v.z), "r"(v.w), "r"((int)rt_ok(i)) : "memory");
    };
    auto tile = [&](int jj) {
      const uint32_t cur = (jj < NST ? jj : jj - NST) * (TILE >> 4);
      if (((0x1012 >> jj) & 1) != 0) mbar_wait(bb + B_KV1 + 8 * ((jj >> 2) - (jj >> 3)), 0);
      if (jj == 8 && wid == 0) {
        mbar_wait(bb + B_EMPTY, 0);
        if (elect_one()) { mbar_expect(bb + B_KV3, 4 * TILE); bulk_g2s(sb, g_kvh + 12 * TILE, 4 * TILE, bb + B_KV3); }
      }
      #pragma unroll
      for (int h = 0; h < 2; h++) {
        uint32_t S[16], P[16];
        WG_FENCE();
        mma_qk_h64<0>(S, qd, kd0 + cur + h * 256); mma_qk_h64<1>(S, qd + 16, kd0 + cur + h * 256 + 16);
        WG_COMMIT();
        WG_WAIT(0); fence_regs<16>(S);
        if (h == 0 && jj == 4) mbar_arrive_if(bb + B_EMPTY, lane == 0);
        exp_part<0, 8>(S, P);
        WG_FENCE();
        mma_pv_h32<1>(O, P, vd0 + cur + h * 256); mma_pv_h32<1>(O, P + 4, vd0 + cur + h * 256 + 64);
        exp_part<8, 8>(S, P);
        WG_FENCE();
        mma_pv_h32<1>(O, P + 8, vd0 + cur + h * 256 + 128); mma_pv_h32<1>(O, P + 12, vd0 + cur + h * 256 + 192);
        WG_COMMIT();
      }
    };
    if (first) {
      int jv = lane >> 6;
      auto step = [&](uint4& v, int ju, int j) {
        if (ju >= 2 && ju < 9) {
          rt_store(j - 2, v);
          if (ju < 6) {
            c8[0] += bf_lo(v.x); c8[1] += bf_hi(v.x); c8[2] += bf_lo(v.y); c8[3] += bf_hi(v.y);
            c8[4] += bf_lo(v.z); c8[5] += bf_hi(v.z); c8[6] += bf_lo(v.w); c8[7] += bf_hi(v.w);
          }
        }
        if (ju < 7) rt_load(j, v);
      };
      #pragma unroll 1
      for (int jj = 0; jj < 10; jj += 2, jv += 2) {
        step(vA, jj, jv); tile(jj);
        step(vB, jj + 1, jv + 1); tile(jj + 1);
      }
    }
    #pragma unroll 1
    for (int jj = first ? 10 : 0; jj < 16; jj++) tile(jj);
    WG_WAIT(0); fence_regs<16>(O);
    if (tid % 128 == 0 && wg != 2) STAMPC(layer * 2, wg, 7);
    const float l0 = __shfl_sync(~0u, O[12], (lane & ~3) | 2), l1 = __shfl_sync(~0u, O[14], (lane & ~3) | 2);
    const bool bad = !(l0 >= L_MIN && l0 < 1e30f) || !(l1 >= L_MIN && l1 < 1e30f) || ((volatile int*)s_misc)[4] != 0;
    slow = __syncthreads_or(bad);
  }
  if (slow) slow_path(G, x0, wq, layer, smem, sb, wg, cta);
  else write_O(G, O, t, r, wg);
  if (first) {
    #pragma unroll
    for (int e = 0; e < 8; e++) { c8[e] += __shfl_xor_sync(~0u, c8[e], 4); c8[e] += __shfl_xor_sync(~0u, c8[e], 8); c8[e] += __shfl_xor_sync(~0u, c8[e], 16); }
    float* s_p2 = (float*)(smem + SM2_OFF);
    if (lane < 4) {
      *(float4*)(s_p2 + wid * 32 + 8 * lane) = make_float4(c8[0], c8[1], c8[2], c8[3]);
      *(float4*)(s_p2 + wid * 32 + 8 * lane + 4) = make_float4(c8[4], c8[5], c8[6], c8[7]);
    }
    __syncthreads();
    if (wid == 4 && cta < 112) {
      float sum = 0.f;
      #pragma unroll
      for (int w = 0; w < 16; w++) sum += s_p2[w * 32 + lane];
      g_cs[(cta < 56 ? 32 * cta : DFF + 32 * (cta - 56)) + lane] = sum;
    }
  }
  if (tid % 128 == 0) { STAMPC(layer * 2, wg, 8); STAMP(layer * 2, wg, 14); }
}

namespace ffn {
constexpr int A_OFF = 0, RING_OFF = 114688, W1_STAGE = 14336, NS1 = 6, STG_OFF = RING_OFF + NS1 * W1_STAGE;
constexpr int STG_WG = 14336;
constexpr int SM_OFF = STG_OFF + 2 * STG_WG;
constexpr int BAR_OFF = SM_OFF;
constexpr int CS_OFF = SM_OFF + 448;
constexpr int SMEM = CS_OFF + 1792;
#define SKEW_STAGES 1
constexpr int HU = 28672, WU = 12544, NS2 = 5, NS2B = 4;
constexpr int B_O = 0, B_SKEW = 7, B_X1 = 8, B_FULL = 15, B_EMPTY = 21, B_WODONE = 27, B_F1DONE = 28, B_STAT = 29, B_SFULL = 30, B_SEMPTY = 32,
              B_FULL2 = 34, B_EMPTY2 = 39, B_FULLB = 44, B_EMPTYB = 48;
__device__ __forceinline__ uint32_t a2_off(int s) { return s * HU; }
__device__ __forceinline__ uint32_t b2_off(int s) { return NS2 * HU + s * WU; }
}

#undef PID
#define PID b
__global__ void __launch_bounds__(384, 1) ffn_kernel(uint8_t* __restrict__ G, const bf16* __restrict__ x0, bf16* __restrict__ out, int layer, int use_role) {
  using namespace ffn;
  extern __shared__ __align__(1024) uint8_t smem[];
  const uint32_t sb = s2u(smem);
  const int tid = threadIdx.x, lane = tid % 32;
  int b = blockIdx.x;
  if (use_role) {
    b = __shfl_sync(~0u, (int)ld_relaxed((const unsigned*)&g_role[smid()]), 0);
    if (tid == 352) red_relaxed(&g_start[2 * layer + 1], 1);
    if (b < 0) {
      if (tid == 0) { pdl_launch(); poll_ge(&g_start[2 * layer + 1], NSM); }
      return;
    }
  }
  const int t = 4 * (b / 32) + (b % 16) / 4, r = 4 * ((b / 16) % 2) + b % 4;
  const int wid = __shfl_sync(~0u, tid / 32, 0), wg = wid / 4;
  const uint32_t bb = sb + BAR_OFF;
  if (tid % 128 == 0) { STAMPC(layer * 2 + 1, wg, 0); STAMP(layer * 2 + 1, wg, 15); }
  if (tid == 0) {
    pdl_launch();
    #pragma unroll
    for (int i = 0; i < 52; i++) {
      int cnt = 1;
      if ((i >= B_EMPTY && i <= B_F1DONE) || (i >= B_EMPTY2 && i < B_FULLB) || i >= B_EMPTYB) cnt = 2;
      if (i == B_STAT) cnt = 64;
      if (i == B_SFULL || i == B_SFULL + 1) cnt = 128;
      if (i == B_SKEW) cnt = 1;
      mbar_init(bb + 8 * i, cnt);
    }
    asm volatile("fence.mbarrier_init.release.cluster;" ::: "memory");
  }

  if (wg == 2) {
    reg_dealloc<40>();
    named_bar(0, 384);
    const int pw = wid - 8;
    if (pw == 1 && elect_one()) {
      #pragma unroll
      for (int j = 0; j < 4; j++) mbar_expect(bb + 8 * (B_O + j), HU + WU);
      if (layer == 1) {
        #pragma unroll
        for (int j = 0; j < 4; j++) bulk_g2s(sb + RING_OFF + j * WU, g_wot + r * 50176 + j * WU, WU, bb + 8 * (B_O + j));
      }
    }
    pdl_wait();
    if (pw == 0) {
      if (elect_one()) {
        if (b == 0) { g_kvcnt[layer] = 0; if (layer == 1) g_start[2] = 0; }
        mbar_wait(bb + 8 * B_WODONE, 0);
        int s = 0, ph = 1;
        #pragma unroll 1
        for (int it = 0; it < 28; it++) {
          mbar_wait(bb + 8 * (B_EMPTY + s), ph);
          mbar_expect(bb + 8 * (B_FULL + s), W1_STAGE);
          bulk_g2s(sb + RING_OFF + s * W1_STAGE, g_w1t + (size_t)(r * 28 + it) * W1_STAGE, W1_STAGE, bb + 8 * (B_FULL + s));
          if (++s == NS1) { s = 0; ph ^= 1; }
        }
      }
      if (elect_one()) {
        mbar_wait(bb + 8 * B_F1DONE, 0);
        int s = 0, ph = 1;
        #pragma unroll 1
        for (int i = 0; i < 16; i++) {
          const int u = i < 8 ? 2 * i : 2 * (i - 8) + 1;
          mbar_wait(bb + 8 * (B_EMPTYB + s), ph);
          mbar_expect(bb + 8 * (B_FULLB + s), WU);
          bulk_g2s(sb + b2_off(s), g_w2t + (size_t)(r * 16 + u) * WU, WU, bb + 8 * (B_FULLB + s));
          if (++s == NS2B) { s = 0; ph ^= 1; }
        }
      }
    } else if (pw == 1) {
      if (elect_one()) {
        #pragma unroll
        for (int j = 0; j < 4; j++) {
          if (layer == 0) bulk_g2s(sb + RING_OFF + j * WU, g_wot + r * 50176 + j * WU, WU, bb + 8 * (B_O + j));
          bulk_g2s(sb + A_OFF + j * HU, g_O + (size_t)t * 114688 + j * HU, HU, bb + 8 * (B_O + j));
        }
      }
      mbar_wait(bb + 8 * B_WODONE, 0);
      poll_ge_warp(&g_x1cnt[layer][t], 2 * 8);
      if (elect_one()) {
        fence_async_global();
        #pragma unroll
        for (int j = 0; j < 4; j++) { mbar_expect(bb + 8 * (B_X1 + j), HU); bulk_g2s(sb + A_OFF + j * HU, g_x1 + (size_t)t * 114688 + j * HU, HU, bb + 8 * (B_X1 + j)); }
      }
      {
        const unsigned* hc = &g_hcnt[layer][t][0];
        #pragma unroll 1
        for (uint32_t it = 0; it < (1u << 21); it++) { if (__all_sync(~0u, ld_relaxed(hc + 2 * (lane & 7)) >= 2)) break; __nanosleep(200); }
        int s = 0, ph = 0;
        #pragma unroll 1
        for (int i = 0; i < 15; i++) {
          const int u = i < 8 ? 2 * i : 2 * ((i - 8) + (i - 8 >= r ? 1 : 0)) + 1;
          if (i == 8) {
            #pragma unroll 1
            for (uint32_t it = 0; it < (1u << 21); it++) { if (__all_sync(~0u, ld_relaxed(hc + 2 * (lane & 7) + 1) >= 2 || (lane & 7) == r)) break; }
          }
          mbar_wait(bb + 8 * (B_EMPTY2 + s), ph);
          if (elect_one()) {
            if (i == 0 || i == 8) fence_async_global();
            mbar_expect(bb + 8 * (B_FULL2 + s), HU);
            bulk_g2s(sb + a2_off(s), g_h + (size_t)(t * 16 + u) * HU, HU, bb + 8 * (B_FULL2 + s));
            STAMP2(2, i);
          }
          if (++s == NS2) { s = 0; ph ^= 1; }
        }
      }
    } else {
      const int i = tid - 320, w = pw - 2;
      float* s_cs = (float*)(smem + CS_OFF);
      #pragma unroll 1
      for (int j = i; j < 448; j += 64) {
        const int nt = j / 224, jj = j % 224;
        s_cs[j] = g_cs[(jj < 112 ? 0 : DFF - 112) + 224 * r + 112 * nt + jj];
      }
      mbar_arrive(bb + 8 * B_STAT);
      if (elect_one()) {
        #pragma unroll 1
        for (int nt = 0; nt < 2; nt++) {
          mbar_wait(bb + 8 * (B_SFULL + w), nt);
          STAMP2(3, w * 16 + nt * 4);
          bulk_s2g(g_h + (size_t)(t * 16 + 2 * r + nt) * HU + w * STG_WG, sb + STG_OFF + w * STG_WG, STG_WG);
          bulk_commit();
          bulk_wait0();
          STAMP2(3, w * 16 + nt * 4 + 1);
          mbar_arrive(bb + 8 * (B_SEMPTY + w));
          red_relaxed(&g_hcnt[layer][t][2 * r + nt], 1);
          STAMP2(3, w * 16 + nt * 4 + 2);
        }
      }
    }
  } else {
    named_bar(0, 384);
    reg_alloc<232>();
    const int warp = wid % 4, g = lane / 4, c = lane % 4, tw = tid % 128;
    const int row0 = wg * 64 + warp * 16 + g;
    const int grow0 = t * 128 + row0, col0 = 56 * r + 2 * c;
    uint32_t xr[14];
    pdl_wait();
    if (tw == 0) STAMPC(layer * 2 + 1, wg, 1);
    {
      #pragma unroll
      for (int j = 0; j < 7; j++) {
        if (layer == 0) {
          xr[2 * j] = __ldg((const uint32_t*)(x0 + (size_t)grow0 * DM + col0 + 8 * j));
          xr[2 * j + 1] = __ldg((const uint32_t*)(x0 + (size_t)(grow0 + 8) * DM + col0 + 8 * j));
        } else {
          const uint32_t o = tiled_off(grow0, col0 + 8 * j);
          xr[2 * j] = __ldg((const uint32_t*)(g_x2 + o)); xr[2 * j + 1] = __ldg((const uint32_t*)(g_x2 + o + 1792));
        }
      }
      float acc[28];
      #pragma unroll
      for (int i = 0; i < 28; i++) acc[i] = 0.f;
      fence_regs<28>(acc);
      const uint64_t ad = mkdesc(SB0 + A_OFF + wg * 14336, 128, 1792, 0), bd = mkdesc(SB0 + RING_OFF, 896, 128, 0);
      #pragma unroll 1
      for (int j = 0; j < 4; j++) {
        mbar_wait(bb + 8 * (B_O + j), 0);
        WG_FENCE();
        #pragma unroll
        for (int ks = 0; ks < 7; ks++) mma_b56_tb(acc, ad + j * 1792 + ks * 16, bd + (j * 7 + ks) * 112, 1);
        WG_COMMIT();
      }
      WG_WAIT(0); fence_regs<28>(acc);
      if (tw == 0) { mbar_arrive(bb + 8 * B_WODONE); STAMPC(layer * 2 + 1, wg, 2); }
      float s0 = 0.f, q0 = 0.f, s1 = 0.f, q1 = 0.f;
      uint8_t* xp = g_x1 + tiled_off(grow0, col0);
      #pragma unroll
      for (int j = 0; j < 7; j++) {
        const uint32_t a = pack_bf16(bf_lo(xr[2 * j]) + acc[4 * j], bf_hi(xr[2 * j]) + acc[4 * j + 1]);
        const uint32_t d = pack_bf16(bf_lo(xr[2 * j + 1]) + acc[4 * j + 2], bf_hi(xr[2 * j + 1]) + acc[4 * j + 3]);
        xr[2 * j] = a; xr[2 * j + 1] = d;
        *(uint32_t*)(xp + j * 128) = a; *(uint32_t*)(xp + j * 128 + 1792) = d;
        s0 += bf_lo(a) + bf_hi(a); q0 = fmaf(bf_lo(a), bf_lo(a), fmaf(bf_hi(a), bf_hi(a), q0));
        s1 += bf_lo(d) + bf_hi(d); q1 = fmaf(bf_lo(d), bf_lo(d), fmaf(bf_hi(d), bf_hi(d), q1));
      }
      uint32_t rb = 0;
      #pragma unroll
      for (int j = 0; j < 7; j++) rb ^= readback(xp + j * 128) ^ readback(xp + j * 128 + 1792);
      #pragma unroll
      for (int o = 1; o < 4; o <<= 1) { s0 += __shfl_xor_sync(~0u, s0, o); q0 += __shfl_xor_sync(~0u, q0, o); s1 += __shfl_xor_sync(~0u, s1, o); q1 += __shfl_xor_sync(~0u, q1, o); }
      if (c < 2) {
        float2* sp = &g_st1[(t * 8 + r) * 128 + row0 + 8 * c];
        *sp = c == 0 ? make_float2(s0, q0) : make_float2(s1, q1);
        rb ^= readback(sp);
      }
      asm volatile("" :: "r"(rb) : "memory");
      named_bar(1 + wg, 128);
      if (tw == 0) red_relaxed(&g_x1cnt[layer][t], 1);
      if (tw == 0) STAMPC(layer * 2 + 1, wg, 3);
    }
    {
      const uint64_t ad = mkdesc(SB0 + A_OFF + wg * 14336, 128, 1792, 0), bd = mkdesc(SB0 + RING_OFF, 3584, 128, 0);
      const float* s_cs = (const float*)(smem + CS_OFF);
      float mu0 = 0.f, mu1 = 0.f, rs0 = 0.f, rs1 = 0.f;
      int s = 0, ph = 0;
      #pragma unroll 1
      for (int nt = 0; nt < 2; nt++) {
        float acc[112];
        #pragma unroll
        for (int i = 0; i < 112; i++) acc[i] = 0.f;
        fence_regs<112>(acc);
        #pragma unroll 1
        for (int kc = 0; kc < 14; kc++) {
          if (nt == 0) mbar_wait(bb + 8 * (B_X1 + (((2 * kc + 1) * 37) >> 8)), 0);
          if (nt == 0 && kc == 2) {
            const float2* sp = g_st1 + (t * 8 + 2 * c) * 128 + row0;
            const float2 p0 = __ldcg(sp), p1 = __ldcg(sp + 128), p2 = __ldcg(sp + 8), p3 = __ldcg(sp + 136);
            float s0 = p0.x + p1.x, q0 = p0.y + p1.y, s1 = p2.x + p3.x, q1 = p2.y + p3.y;
            #pragma unroll
            for (int o = 1; o < 4; o <<= 1) { s0 += __shfl_xor_sync(~0u, s0, o); q0 += __shfl_xor_sync(~0u, q0, o); s1 += __shfl_xor_sync(~0u, s1, o); q1 += __shfl_xor_sync(~0u, q1, o); }
            mu0 = s0 * (1.f / DM); mu1 = s1 * (1.f / DM);
            rs0 = rsqrtf(fmaxf(q0 * (1.f / DM) - mu0 * mu0, 0.f) + 1e-5f); rs1 = rsqrtf(fmaxf(q1 * (1.f / DM) - mu1 * mu1, 0.f) + 1e-5f);
          }
          if (wg == 1 && nt == 0 && kc == 0) mbar_wait(bb + 8 * B_SKEW, 0);
          mbar_wait(bb + 8 * (B_FULL + s), ph);
          if (kc == 0 && tw == 0) STAMPC(layer * 2 + 1, wg, 4 + 3 * nt);
          const int k0 = 2 * kc, k1 = 2 * kc + 1;
          const uint32_t u0 = (k0 * 37) >> 8, u1 = (k1 * 37) >> 8;
          const uint64_t a0 = ad + k0 * 16 + u0 * 1680, a1 = ad + k1 * 16 + u1 * 1680, w = bd + s * (W1_STAGE >> 4);
          WG_FENCE();
          mma_b224_tb(acc, a0, w, 1); mma_b224_tb(acc, a1, w + 448, 1);
          WG_COMMIT();
          if (wg == 0 && nt == 0 && kc == SKEW_STAGES - 1 && tw == 0) mbar_arrive(bb + 8 * B_SKEW);
          if (kc > 0) {
            WG_WAIT(1);
            if (tw == 0) {
              mbar_arrive(bb + 8 * (B_EMPTY + (s == 0 ? NS1 - 1 : s - 1)));
              if (nt == 1 && (kc == 4 || kc == 7 || kc == 11)) mbar_arrive(bb + 8 * (B_EMPTY2 + (kc == 4 ? 0 : (kc == 7 ? 1 : 2))));
            }
          }
          if (++s == NS1) { s = 0; ph ^= 1; }
        }
        WG_WAIT(0); fence_regs<112>(acc);
        if (tw == 0) { mbar_arrive(bb + 8 * (B_EMPTY + (s == 0 ? NS1 - 1 : s - 1))); if (nt == 1) { mbar_arrive(bb + 8 * B_F1DONE); mbar_arrive(bb + 8 * (B_EMPTY2 + 3)); mbar_arrive(bb + 8 * (B_EMPTY2 + 4)); } STAMPC(layer * 2 + 1, wg, 5 + 3 * nt); }
        if (nt == 0) mbar_wait(bb + 8 * B_STAT, 0); else mbar_wait(bb + 8 * (B_SEMPTY + wg), 0);
        const float ka0 = 0.7978845608028654f * rs0, kb0 = 0.035677408136300125f * rs0 * rs0 * rs0, hh0 = 0.5f * rs0 * rs0;
        const float ka1 = 0.7978845608028654f * rs1, kb1 = 0.035677408136300125f * rs1 * rs1 * rs1, hh1 = 0.5f * rs1 * rs1;
        const uint32_t sta = sb + STG_OFF + wg * STG_WG + (warp * 2 + ((lane >> 3) & 1)) * 1792 + (lane >> 4) * 128 + (lane & 7) * 16;
        #pragma unroll
        for (int j = 0; j < 14; j++) {
          const float2 cg = *(const float2*)(s_cs + 224 * nt + 8 * j + 2 * c), cu = *(const float2*)(s_cs + 224 * nt + 112 + 8 * j + 2 * c);
          #pragma unroll
          for (int e = 0; e < 4; e++) {
            const float mu = e < 2 ? mu0 : mu1, ka = e < 2 ? ka0 : ka1, kb = e < 2 ? kb0 : kb1, hh = e < 2 ? hh0 : hh1;
            const float tg = fmaf(-mu, (e & 1) ? cg.y : cg.x, acc[4 * j + e]);
            const float tu = fmaf(-mu, (e & 1) ? cu.y : cu.x, acc[56 + 4 * j + e]);
            acc[4 * j + e] = tg * fmaf(kb, tg * tg, ka);
            acc[56 + 4 * j + e] = (tg * hh) * tu;
          }
        }
        #pragma unroll
        for (int j2 = 0; j2 < 7; j2++) {
          uint32_t hp[4];
          #pragma unroll
          for (int q = 0; q < 4; q++) {
            const int i0 = 8 * j2 + 2 * q;
            const float t0 = tanhf_fast(acc[i0]), t1 = tanhf_fast(acc[i0 + 1]);
            hp[q] = pack_bf16(fmaf(acc[56 + i0], t0, acc[56 + i0]), fmaf(acc[56 + i0 + 1], t1, acc[56 + i0 + 1]));
          }
          stmatrix_x4(sta + j2 * 256, hp[0], hp[1], hp[2], hp[3]);
        }
        fence_async_smem();
        mbar_arrive(bb + 8 * (B_SFULL + wg));
        if (nt == 1) named_bar(1 + wg, 128);
        if (tw == 0) STAMPC(layer * 2 + 1, wg, 6 + 3 * nt);
      }
    }
    {
      float acc[28];
      #pragma unroll
      for (int i = 0; i < 28; i++) acc[i] = 0.f;
      fence_regs<28>(acc);
      int s = 0, ph = 0, sB = 0, phB = 0;
      #pragma unroll 1
      for (int i = 0; i < 16; i++) {
        mbar_wait(bb + 8 * (B_FULLB + sB), phB);
        if (tw == 0) STAMP2(wg, 16 + i);
        const bool own = i == 8 + r;
        if (!own) mbar_wait(bb + 8 * (B_FULL2 + s), ph);
        if (tw == 0) STAMP2(wg, i);
        if (tw == 0 && i == 0) STAMPC(layer * 2 + 1, wg, 10);
        if (tw == 0 && i == 8) STAMPC(layer * 2 + 1, wg, 11);
        const uint64_t a = mkdesc(SB0 + (own ? STG_OFF : a2_off(s)) + wg * 14336, 128, 1792, 0), w = mkdesc(SB0 + b2_off(sB), 896, 128, 0);
        WG_FENCE();
        #pragma unroll
        for (int ks = 0; ks < 7; ks++) mma_b56_tb(acc, a + ks * 16, w + ks * 112, 1);
        WG_COMMIT();
        if (i > 0) {
          WG_WAIT(1);
          if (tw == 0) {
            if (i != 9 + r) mbar_arrive(bb + 8 * (B_EMPTY2 + (s == 0 ? NS2 - 1 : s - 1)));
            mbar_arrive(bb + 8 * (B_EMPTYB + (sB == 0 ? NS2B - 1 : sB - 1)));
          }
        }
        if (!own && ++s == NS2) { s = 0; ph ^= 1; }
        if (++sB == NS2B) { sB = 0; phB ^= 1; }
      }
      WG_WAIT(0); fence_regs<28>(acc);
      if (tw == 0) STAMPC(layer * 2 + 1, wg, 12);
      float s0 = 0.f, q0 = 0.f, s1 = 0.f, q1 = 0.f;
      #pragma unroll
      for (int j = 0; j < 7; j++) {
        const uint32_t a = pack_bf16(bf_lo(xr[2 * j]) + acc[4 * j], bf_hi(xr[2 * j]) + acc[4 * j + 1]);
        const uint32_t d = pack_bf16(bf_lo(xr[2 * j + 1]) + acc[4 * j + 2], bf_hi(xr[2 * j + 1]) + acc[4 * j + 3]);
        if (layer == 0) {
          const uint32_t o = tiled_off(grow0, col0 + 8 * j);
          *(uint32_t*)(g_x2 + o) = a; *(uint32_t*)(g_x2 + o + 1792) = d;
        } else {
          *(uint32_t*)(out + (size_t)grow0 * DM + col0 + 8 * j) = a;
          *(uint32_t*)(out + (size_t)(grow0 + 8) * DM + col0 + 8 * j) = d;
        }
        s0 += bf_lo(a) + bf_hi(a); q0 = fmaf(bf_lo(a), bf_lo(a), fmaf(bf_hi(a), bf_hi(a), q0));
        s1 += bf_lo(d) + bf_hi(d); q1 = fmaf(bf_lo(d), bf_lo(d), fmaf(bf_hi(d), bf_hi(d), q1));
      }
      if (layer == 0) {
        #pragma unroll
        for (int o = 1; o < 4; o <<= 1) { s0 += __shfl_xor_sync(~0u, s0, o); q0 += __shfl_xor_sync(~0u, q0, o); s1 += __shfl_xor_sync(~0u, s1, o); q1 += __shfl_xor_sync(~0u, q1, o); }
        if (c == 0) { g_st2[(t * 8 + r) * 128 + row0] = make_float2(s0, q0); g_st2[(t * 8 + r) * 128 + row0 + 8] = make_float2(s1, q1); }
      }
      if (tw == 0) { STAMPC(layer * 2 + 1, wg, 13); STAMP(layer * 2 + 1, wg, 14); }
    }
  }
}
static_assert(ffn::SMEM <= 232448, "smem");
static_assert(attn::SMEM <= 232448, "smem");

#define USE_ROLE 1
typedef CUresult (*EncodeFn)(CUtensorMap*, CUtensorMapDataType, cuuint32_t, void*, const cuuint64_t*, const cuuint64_t*, const cuuint32_t*,
                             const cuuint32_t*, CUtensorMapInterleave, CUtensorMapSwizzle, CUtensorMapL2promotion, CUtensorMapFloatOOBfill);
static void make_map(EncodeFn enc, CUtensorMap* m, const void* p, uint64_t cols, uint64_t rows, uint32_t bc, uint32_t br) {
  cuuint64_t dims[2] = {cols, rows};
  cuuint64_t strides[1] = {cols * 2};
  cuuint32_t box[2] = {bc, br};
  cuuint32_t es[2] = {1, 1};
  enc(m, CU_TENSOR_MAP_DATA_TYPE_BFLOAT16, 2, const_cast<void*>(p), dims, strides, box, es, CU_TENSOR_MAP_INTERLEAVE_NONE,
      CU_TENSOR_MAP_SWIZZLE_128B, CU_TENSOR_MAP_L2_PROMOTION_L2_128B, CU_TENSOR_MAP_FLOAT_OOB_FILL_NONE);
}

extern "C" void kernel_launch(void* const* d_in, const int* in_sizes, int n_in, void* d_out, int out_size) {
  (void)in_sizes; (void)n_in; (void)out_size;
  const bf16* x = (const bf16*)d_in[0];
  const bf16* wq = (const bf16*)d_in[1];
  const bf16* wk = (const bf16*)d_in[2];
  const bf16* wv = (const bf16*)d_in[3];
  const bf16* wo = (const bf16*)d_in[4];
  const bf16* wgate = (const bf16*)d_in[6];
  const bf16* wup = (const bf16*)d_in[7];
  const bf16* wdown = (const bf16*)d_in[8];

  static uint8_t* G = nullptr;
  static EncodeFn enc = nullptr;
  static int use_role = 0;
  if (!G) {
    int dev = 0, nsm = 0;
    cudaGetDevice(&dev);
    cudaDeviceGetAttribute(&nsm, cudaDevAttrMultiProcessorCount, dev);
    use_role = (nsm == NSM && USE_ROLE) ? 1 : 0;
    void* fn = nullptr; cudaDriverEntryPointQueryResult st;
    cudaGetDriverEntryPoint("cuTensorMapEncodeTiled", &fn, cudaEnableDefault, &st);
    enc = (EncodeFn)fn;
    cudaGetSymbolAddress((void**)&G, g_scratch);
    cudaFuncSetAttribute(attn_kernel, cudaFuncAttributeMaxDynamicSharedMemorySize, attn::SMEM);
    cudaFuncSetAttribute(ffn_kernel, cudaFuncAttributeMaxDynamicSharedMemorySize, ffn::SMEM);
  }
  CUtensorMap tm_x, tm_wq;
  make_map(enc, &tm_x, x, DM, SEQ, 64, 64);
  make_map(enc, &tm_wq, wq, DM, DM, 64, 224);
  cudaLaunchAttribute pdl[1];
  pdl[0].id = cudaLaunchAttributeProgrammaticStreamSerialization;
  pdl[0].val.programmaticStreamSerializationAllowed = 1;
  cudaLaunchConfig_t cfg = {};
  cfg.stream = cudaStreamPerThread;
#define NLAYERS 2
  const int grid = use_role ? NSM : 128;
  for (int layer = 0; layer < NLAYERS; layer++) {
    cfg.gridDim = dim3(grid); cfg.blockDim = dim3(512); cfg.dynamicSmemBytes = attn::SMEM;
    cfg.attrs = pdl; cfg.numAttrs = layer > 0 ? 1 : 0;
    cudaLaunchKernelEx(&cfg, attn_kernel, tm_x, tm_wq, G, x, wq, wk, wv, wo, wgate, wup, wdown, layer, use_role);
    cfg.gridDim = dim3(grid); cfg.blockDim = dim3(384); cfg.dynamicSmemBytes = ffn::SMEM;
    cfg.attrs = pdl; cfg.numAttrs = use_role ? 1 : 0;
    cudaLaunchKernelEx(&cfg, ffn_kernel, G, x, (bf16*)d_out, layer, use_role);
  }
}
```
